```python
import torch

def _softmax(x, axis=-1):
    return torch.softmax(x, dim=axis)
def _gelu(x):
    return torch.nn.functional.gelu(x, approximate="tanh")
def _silu(x):
    return torch.nn.functional.silu(x)
def _sigmoid(x):
    return torch.sigmoid(x)
def _layernorm(x, axis=-1, eps=1e-5):
    m = x.mean(dim=axis, keepdim=True)
    v = x.var(dim=axis, keepdim=True, unbiased=False)
    return (x - m) / torch.sqrt(v + eps)
def _scatter_add(tgt, idx, src, axis=0):
    return tgt.clone().index_add_(axis, idx, src)
def _segment_sum(src, seg, n):
    out = torch.zeros((n,) + src.shape[1:], dtype=src.dtype)
    return out.index_add_(0, seg, src)
def _pad(x, pw):
    flat = tuple(v for pair in reversed(pw) for v in pair)
    return torch.nn.functional.pad(x, flat)

kernel_name = 'parallel_sum__linear_attn_block__glu_gated_geglu__prompt'

def setup_inputs():

    _w = (lambda a: (lambda t: t.to(torch.bfloat16) if t.is_floating_point() else t)(torch.as_tensor(a)))
    def _A_setup():
        B, S, D = 1, 2048, 512
        return {
            "x": _w((lambda *s: torch.randn(*s, dtype=torch.bfloat16) * 0.05)(B, S, D)),
            "wqkv": _w((lambda *s: torch.randn(*s, dtype=torch.bfloat16) * 0.1)(D, 3 * D)),
            "wo": _w((lambda *s: torch.randn(*s, dtype=torch.bfloat16) * 0.05)(D, D)),
        }
    _A_in = _A_setup()

    def _B_setup():
        B, S, Dm, Df = 1, 2048, 512, 1376
        return {
            "x": _w((lambda *s: torch.randn(*s, dtype=torch.bfloat16) * 0.05)(B, S, Dm)),
            "w_gate": _w((lambda *s: torch.randn(*s, dtype=torch.bfloat16) * 0.4)(Dm, Df) * (Dm ** -0.5)),
            "w_up": _w((lambda *s: torch.randn(*s, dtype=torch.bfloat16) * 0.4)(Dm, Df) * (Dm ** -0.5)),
            "w_down": _w((lambda *s: torch.randn(*s, dtype=torch.bfloat16) * 0.4)(Df, Dm) * (Df ** -0.5)),
        }
    _B_in = _B_setup()

    return {
        "A_x": _A_in["x"],
        "A_wqkv": _A_in["wqkv"],
        "A_wo": _A_in["wo"],
        "B_x": _B_in["x"],
        "B_w_gate": _B_in["w_gate"],
        "B_w_up": _B_in["w_up"],
        "B_w_down": _B_in["w_down"],
    }

def reference(A_x, A_wqkv, A_wo, B_x, B_w_gate, B_w_up, B_w_down):
    def _A_ref(x, wqkv, wo):
        B, S, D = x.shape
        H = 32; Dh = D // H
        qkv = (lambda x, *d: x.permute(*d))((x @ wqkv).reshape(B, S, 3, H, Dh), 2, 0, 3, 1, 4)
        q, k, v = qkv[0], qkv[1], qkv[2]
        phi = lambda t: torch.where(t > 0, t + 1, torch.exp(t)) + 1e-6
        pq, pk = phi(q), phi(k)
        kv = torch.einsum("bhsd,bhse->bhde", pk, v)
        z = torch.einsum("bhsd->bhd", pk)
        num = torch.einsum("bhqd,bhde->bhqe", pq, kv)
        den = torch.einsum("bhqd,bhd->bhq", pq, z)[..., None] + 1e-6
        o = num / den
        return (lambda x, *d: x.permute(*d))(o, 0, 2, 1, 3).reshape(B, S, D) @ wo

    def _B_ref(x, w_gate, w_up, w_down):
        g = torch.einsum("bsd,df->bsf", x, w_gate)
        u = torch.einsum("bsd,df->bsf", x, w_up)
        h = _gelu(g) * u
        return torch.einsum("bsf,fd->bsd", h, w_down)

    x = A_x
    xn = _layernorm(x, axis=-1)
    return x + _A_ref(xn, A_wqkv, A_wo) + _B_ref(xn, B_w_gate, B_w_up, B_w_down)
```

```cpp
#include <cuda_runtime.h>
#include <cuda_bf16.h>
#include <cuda.h>
#include <stdint.h>

#define RED_PACE 0
#define LAST64
#define NHB 4
#define RED_MODE 1
#define PB 0
#define INIT_AT 10
#define PFW_AT 9
#define PFMODE 2
#define MERGEB 1
namespace fk {

constexpr int S_ = 2048, D_ = 512, DF_ = 1376;
constexpr int FS = 176;
constexpr int NSTEP = 48;

constexpr int OFF_X = 0;
constexpr int OFF_RING = 131072;
constexpr int OFF_KVT = OFF_RING + 65536;
constexpr int OFF_KVB = OFF_RING + 81920;
constexpr int OFF_FULL = OFF_KVB + 1024 + 8704;
constexpr int OFF_EMPTY = OFF_FULL + NSTEP * 8;
constexpr int OFF_BAR = OFF_EMPTY + NSTEP * 8;
constexpr int BAR_LNQ = OFF_BAR + 0, BAR_KVD = OFF_BAR + 8, BAR_KVR = OFF_BAR + 16, BAR_CPY = OFF_BAR + 24, BAR_INI = OFF_BAR + 32;
constexpr int BAR_STG = OFF_BAR + 40;
constexpr int BAR_LN = OFF_BAR + 72;
constexpr int BAR_KPF = OFF_BAR + 104;
constexpr int BAR_DRN = OFF_BAR + 136;
constexpr int BAR_RCV = OFF_BAR + 160;
constexpr int BAR_PEER = OFF_BAR + 224;
constexpr int OFF_PAR = OFF_BAR + 248;
constexpr int BAR_ST2 = OFF_BAR + 256;
constexpr int OFF_CS = OFF_BAR + 384;
constexpr int OFF_KVF = OFF_CS + 2304;
constexpr int OFF_PROF = OFF_KVF + 3072;
constexpr int SMEM_BYTES = OFF_PROF + 256 + 1024;
static_assert(OFF_KVF % 128 == 0, "align");

__host__ __device__ constexpr int ring_slot(int t) {
  return t < 13 ? (t - 8 + 3) % 5 : (t < 20 ? (t - 13 + 3) % 4 : ((t - 20) % 5 == 0 ? 4 : ((t - 20) % 5 + 1) % 4));
}
__host__ __device__ constexpr int ring_off(int t) {
  return t < 8 ? OFF_RING + (t % 3) * 24576
               : (t < 37 ? OFF_RING + ring_slot(t) * 16384
                         : (t < 41 ? OFF_X + (t - 33) * 16384 : (t < 46 ? OFF_RING + ring_slot(t - 9) * 16384 : OFF_X + (t - 42) * 16384)));
}
__host__ __device__ constexpr int ring_dep(int t) {
  return t >= 41 ? t - 9 : (t >= 37 ? 31 : (t > 20 ? t - 5 : (t == 20 ? 9 : (t >= 14 ? t - 4 : (t == 13 ? 8 : (t < 10 ? 5 : (t == 10 ? 6 : 7)))))));
}

__device__ unsigned long long g_cs[8][9][64];
__device__ float g_kv[2][8][1152];
__device__ unsigned g_flagR[16][32];
__device__ unsigned g_flagK[8][32];
__device__ unsigned g_epoch[132 * 8];
#define PROF(i)
#define PROFL(i)
#define PROFG(i)

struct Maps { CUtensorMap x, qkv, g, u, wo, wd, out, qkv2, out64; };

__device__ __forceinline__ uint32_t smem_u32(const void* p) { return (uint32_t)__cvta_generic_to_shared(p); }
__device__ __forceinline__ bool elect_one() {
  uint32_t p;
  asm volatile("{\n.reg .pred P;\nelect.sync _|P, 0xffffffff;\nselp.u32 %0, 1, 0, P;\n}" : "=r"(p));
  return p != 0;
}
__device__ __forceinline__ void mbar_init(uint32_t bar, int count) {
  asm volatile("mbarrier.init.shared::cta.b64 [%0], %1;" ::"r"(bar), "r"(count) : "memory");
}
__device__ __forceinline__ void mbar_expect_tx(uint32_t bar, uint32_t bytes) {
  asm volatile("mbarrier.arrive.expect_tx.shared::cta.b64 _, [%0], %1;" ::"r"(bar), "r"(bytes) : "memory");
}
__device__ __forceinline__ void mbar_arrive(uint32_t bar) {
  asm volatile("mbarrier.arrive.shared::cta.b64 _, [%0];" ::"r"(bar) : "memory");
}
__device__ __forceinline__ void mbar_wait(uint32_t bar) {
  asm volatile(
      "{\n.reg .pred p;\n.reg .u32 c;\nmov.u32 c, 0;\n"
      "W_%=:\n"
      "mbarrier.try_wait.parity.shared::cta.b64 p, [%0], 0;\n"
      "@p bra D_%=;\n"
      "add.u32 c, c, 1;\n"
      "setp.lt.u32 p, c, 50000;\n"
      "@p bra W_%=;\n"
      "D_%=:\n}\n" ::"r"(bar)
      : "memory");
}
__device__ __forceinline__ uint32_t mbar_test(uint32_t bar) {
  uint32_t ok;
  asm volatile("{\n.reg .pred p;\nmbarrier.test_wait.parity.shared::cta.b64 p, [%1], 0;\nselp.u32 %0, 1, 0, p;\n}" : "=r"(ok) : "r"(bar) : "memory");
  return ok;
}
__device__ __forceinline__ void mbar_wait_par(uint32_t bar, uint32_t parity) {
  asm volatile(
      "{\n.reg .pred p;\n.reg .u32 c;\nmov.u32 c, 0;\n"
      "W_%=:\n"
      "mbarrier.try_wait.parity.shared::cta.b64 p, [%0], %1;\n"
      "@p bra D_%=;\n"
      "add.u32 c, c, 1;\n"
      "setp.lt.u32 p, c, 50000;\n"
      "@p bra W_%=;\n"
      "D_%=:\n}\n" ::"r"(bar), "r"(parity)
      : "memory");
}
__device__ __forceinline__ void tma2d(uint32_t dst, const CUtensorMap* map, int c0, int c1, uint32_t bar) {
  asm volatile(
      "cp.async.bulk.tensor.2d.shared::cluster.global.mbarrier::complete_tx::bytes [%0], [%1, {%3, %4}], [%2];" ::"r"(dst),
      "l"(map), "r"(bar), "r"(c0), "r"(c1)
      : "memory");
}
__device__ __forceinline__ void tma3d(uint32_t dst, const CUtensorMap* map, int c0, int c1, int c2, uint32_t bar) {
  asm volatile(
      "cp.async.bulk.tensor.3d.shared::cluster.global.mbarrier::complete_tx::bytes [%0], [%1, {%3, %4, %5}], [%2];" ::"r"(dst),
      "l"(map), "r"(bar), "r"(c0), "r"(c1), "r"(c2)
      : "memory");
}
__device__ __forceinline__ void prefetch_map(const CUtensorMap* map) {
  asm volatile("prefetch.tensormap [%0];" ::"l"(map) : "memory");
}
__device__ __forceinline__ void wg_fence() { asm volatile("wgmma.fence.sync.aligned;" ::: "memory"); }
__device__ __forceinline__ void wg_commit() { asm volatile("wgmma.commit_group.sync.aligned;" ::: "memory"); }
template <int N>
__device__ __forceinline__ void wg_wait() { asm volatile("wgmma.wait_group.sync.aligned %0;" ::"n"(N) : "memory"); }
__device__ __forceinline__ uint32_t pack_bf16(float lo, float hi) {
  uint32_t r;
  asm volatile("cvt.rn.bf16x2.f32 %0, %1, %2;" : "=r"(r) : "f"(hi), "f"(lo));
  return r;
}
__device__ __forceinline__ uint32_t bsub2(uint32_t a, uint32_t b) { uint32_t r; asm("sub.rn.bf16x2 %0, %1, %2;" : "=r"(r) : "r"(a), "r"(b)); return r; }
__device__ __forceinline__ uint32_t badd2(uint32_t a, uint32_t b) { uint32_t r; asm("add.rn.bf16x2 %0, %1, %2;" : "=r"(r) : "r"(a), "r"(b)); return r; }
__device__ __forceinline__ uint32_t bmul2(uint32_t a, uint32_t b) { uint32_t r; asm("mul.rn.bf16x2 %0, %1, %2;" : "=r"(r) : "r"(a), "r"(b)); return r; }
__device__ __forceinline__ uint32_t bfma2(uint32_t a, uint32_t b, uint32_t c) { uint32_t r; asm("fma.rn.bf16x2 %0, %1, %2, %3;" : "=r"(r) : "r"(a), "r"(b), "r"(c)); return r; }
__device__ __forceinline__ void stsm4(uint32_t addr, uint32_t a0, uint32_t a1, uint32_t a2, uint32_t a3) {
  asm volatile("stmatrix.sync.aligned.m8n8.x4.shared.b16 [%0], {%1,%2,%3,%4};" ::"r"(addr), "r"(a0), "r"(a1), "r"(a2), "r"(a3) : "memory");
}
__device__ __forceinline__ void ldsm4(uint32_t (&r)[4], uint32_t addr) {
  asm volatile("ldmatrix.sync.aligned.m8n8.x4.shared.b16 {%0,%1,%2,%3}, [%4];"
               : "=r"(r[0]), "=r"(r[1]), "=r"(r[2]), "=r"(r[3]) : "r"(addr) : "memory");
}
__device__ __forceinline__ void sts32(uint32_t a, uint32_t v) { asm volatile("st.shared.u32 [%0], %1;" ::"r"(a), "r"(v) : "memory"); }
__device__ __forceinline__ void fence_async_smem() { asm volatile("fence.proxy.async.shared::cta;" ::: "memory"); }
__device__ __forceinline__ void prefetch_l2(const void* p, uint32_t bytes) {
  asm volatile("cp.async.bulk.prefetch.L2.global [%0], %1;" ::"l"(p), "r"(bytes) : "memory");
}
__device__ __forceinline__ void red_v4(float* p, float a, float b, float c, float d) {
  asm volatile("red.relaxed.gpu.global.add.v4.f32 [%0], {%1,%2,%3,%4};" ::"l"(p), "f"(a), "f"(b), "f"(c), "f"(d) : "memory");
}
__device__ __forceinline__ uint32_t atom_v4(float* p, float a, float b, float c, float d) {
  float r0, r1, r2, r3;
  asm volatile("atom.relaxed.gpu.global.add.v4.f32 {%0,%1,%2,%3}, [%4], {%5,%6,%7,%8};"
               : "=f"(r0), "=f"(r1), "=f"(r2), "=f"(r3) : "l"(p), "f"(a), "f"(b), "f"(c), "f"(d) : "memory");
  return __float_as_uint(r0);
}
__device__ __forceinline__ void consume(uint32_t v, uint32_t dummy_smem) {
  asm volatile("{\n.reg .pred p;\nsetp.eq.u32 p, %0, 0x7fc1a5e3;\n@p st.shared.u32 [%1], %0;\n}" ::"r"(v), "r"(dummy_smem) : "memory");
}
__device__ __forceinline__ void st_async4(uint32_t addr, uint32_t a, uint32_t b, uint32_t c, uint32_t d, uint32_t bar) {
  asm volatile("st.async.weak.shared::cluster.mbarrier::complete_tx::bytes.v4.u32 [%0], {%1,%2,%3,%4}, [%5];" ::"r"(addr),
               "r"(a), "r"(b), "r"(c), "r"(d), "r"(bar) : "memory");
}
__device__ __forceinline__ void red_bf16x8(void* p, uint4 v) {
  asm volatile("red.relaxed.gpu.global.add.noftz.v4.bf16x2 [%0], {%1,%2,%3,%4};" ::"l"(p), "r"(v.x), "r"(v.y), "r"(v.z), "r"(v.w) : "memory");
}
__device__ __forceinline__ float ex2f(float x) { float r; asm("ex2.approx.ftz.f32 %0, %1;" : "=f"(r) : "f"(x)); return r; }
__device__ __forceinline__ float tanhf_(float x) { float r; asm("tanh.approx.f32 %0, %1;" : "=f"(r) : "f"(x)); return r; }
__device__ __forceinline__ float rcpf_(float x) { float r; asm("rcp.approx.ftz.f32 %0, %1;" : "=f"(r) : "f"(x)); return r; }
__device__ __forceinline__ float2 lds64f(uint32_t a) {
  float2 v;
  asm volatile("ld.shared.v2.f32 {%0,%1}, [%2];" : "=f"(v.x), "=f"(v.y) : "r"(a) : "memory");
  return v;
}
__device__ __forceinline__ uint4 lds128(uint32_t a) {
  uint4 v;
  asm volatile("ld.shared.v4.u32 {%0,%1,%2,%3}, [%4];" : "=r"(v.x), "=r"(v.y), "=r"(v.z), "=r"(v.w) : "r"(a) : "memory");
  return v;
}
__device__ __forceinline__ uint2 lds64(uint32_t a) {
  uint2 v;
  asm volatile("ld.shared.v2.u32 {%0,%1}, [%2];" : "=r"(v.x), "=r"(v.y) : "r"(a) : "memory");
  return v;
}
__device__ __forceinline__ void sts128(uint32_t a, uint4 v) {
  asm volatile("st.shared.v4.u32 [%0], {%1,%2,%3,%4};" ::"r"(a), "r"(v.x), "r"(v.y), "r"(v.z), "r"(v.w) : "memory");
}
__device__ __forceinline__ uint4 ldg128(const void* p) {
  uint4 v;
  asm volatile("ld.global.nc.v4.u32 {%0,%1,%2,%3}, [%4];" : "=r"(v.x), "=r"(v.y), "=r"(v.z), "=r"(v.w) : "l"(p));
  return v;
}
__device__ __forceinline__ uint4 ldcg128(const void* p) {
  uint4 v;
  asm volatile("ld.relaxed.gpu.global.v4.u32 {%0,%1,%2,%3}, [%4];" : "=r"(v.x), "=r"(v.y), "=r"(v.z), "=r"(v.w) : "l"(p) : "memory");
  return v;
}
__device__ __forceinline__ unsigned ldcg32(const unsigned* p) {
  unsigned v;
  asm volatile("ld.relaxed.gpu.global.u32 %0, [%1];" : "=r"(v) : "l"(p) : "memory");
  return v;
}
__device__ __forceinline__ void fence_gpu() { asm volatile("fence.acq_rel.gpu;" ::: "memory"); }
__device__ __forceinline__ void st_flag(unsigned* p, unsigned v) {
  asm volatile("st.relaxed.gpu.global.u32 [%0], %1;" ::"l"(p), "r"(v) : "memory");
}
__device__ __forceinline__ void wait_flags(const unsigned* p, bool active, unsigned tag) {
#pragma unroll 1
  for (int it = 0; it < 20000; it++) {
    unsigned x = tag;
    if (active) asm volatile("ld.acquire.gpu.global.u32 %0, [%1];" : "=r"(x) : "l"(p) : "memory");
    if (__all_sync(0xffffffffu, x == tag)) break;
    __nanosleep(40);
  }
}
template <int ID, int N>
__device__ __forceinline__ void bar_sync() { asm volatile("bar.sync %0, %1;" ::"n"(ID), "n"(N) : "memory"); }
__device__ __forceinline__ float bflo(uint32_t u) { return __uint_as_float(u << 16); }
__device__ __forceinline__ float bfhi(uint32_t u) { return __uint_as_float(u & 0xffff0000u); }

template <int I> struct IC { static constexpr int v = I; };
template <int I, int N, class F>
__device__ __forceinline__ void static_for(F&& f) {
  if constexpr (I < N) { f(IC<I>{}); static_for<I + 1, N>(f); }
}
#define SFOR(var, N) static_for<0, N>([&](auto var##_) __attribute__((always_inline)) { constexpr int var = decltype(var##_)::v;
#define SEND });

template <int AOFF, int BOFF, int SCALE, unsigned BHI = 0x40000040u, unsigned AHI = 0x40000040u, int TA = 0, int TB = 1>
__device__ __forceinline__ void wgmma_ss_n128(float* d, uint32_t alo, uint32_t blo) {
  if constexpr (SCALE == 1) {
  asm volatile("{\n.reg .b32 ta, tb;\n.reg .b64 da, db;\n"
    "add.u32 ta, %64, %66;\nmov.b64 da, {ta, %69};\n"
    "add.u32 tb, %65, %67;\nmov.b64 db, {tb, %68};\n"
    "wgmma.mma_async.sync.aligned.m64n128k16.f32.bf16.bf16 "
    "{%0, %1, %2, %3, %4, %5, %6, %7, %8, %9, %10, %11, %12, %13, %14, %15, "
    "%16, %17, %18, %19, %20, %21, %22, %23, %24, %25, %26, %27, %28, %29, %30, %31, "
    "%32, %33, %34, %35, %36, %37, %38, %39, %40, %41, %42, %43, %44, %45, %46, %47, "
    "%48, %49, %50, %51, %52, %53, %54, %55, %56, %57, %58, %59, %60, %61, %62, %63}, "
    "da, db, 1, 1, 1, %70, %71;\n}\n"
    : "+f"(d[0]), "+f"(d[1]), "+f"(d[2]), "+f"(d[3]), "+f"(d[4]), "+f"(d[5]), "+f"(d[6]), "+f"(d[7]),
      "+f"(d[8]), "+f"(d[9]), "+f"(d[10]), "+f"(d[11]), "+f"(d[12]), "+f"(d[13]), "+f"(d[14]), "+f"(d[15]),
      "+f"(d[16]), "+f"(d[17]), "+f"(d[18]), "+f"(d[19]), "+f"(d[20]), "+f"(d[21]), "+f"(d[22]), "+f"(d[23]),
      "+f"(d[24]), "+f"(d[25]), "+f"(d[26]), "+f"(d[27]), "+f"(d[28]), "+f"(d[29]), "+f"(d[30]), "+f"(d[31]),
      "+f"(d[32]), "+f"(d[33]), "+f"(d[34]), "+f"(d[35]), "+f"(d[36]), "+f"(d[37]), "+f"(d[38]), "+f"(d[39]),
      "+f"(d[40]), "+f"(d[41]), "+f"(d[42]), "+f"(d[43]), "+f"(d[44]), "+f"(d[45]), "+f"(d[46]), "+f"(d[47]),
      "+f"(d[48]), "+f"(d[49]), "+f"(d[50]), "+f"(d[51]), "+f"(d[52]), "+f"(d[53]), "+f"(d[54]), "+f"(d[55]),
      "+f"(d[56]), "+f"(d[57]), "+f"(d[58]), "+f"(d[59]), "+f"(d[60]), "+f"(d[61]), "+f"(d[62]), "+f"(d[63])
    : "r"(alo), "r"(blo), "n"(AOFF >> 4), "n"(BOFF >> 4), "n"(BHI), "n"(AHI), "n"(TA), "n"(TB));
  } else if constexpr (SCALE == 0) {
  asm volatile("{\n.reg .b32 ta, tb;\n.reg .b64 da, db;\n"
    "add.u32 ta, %64, %66;\nmov.b64 da, {ta, %69};\n"
    "add.u32 tb, %65, %67;\nmov.b64 db, {tb, %68};\n"
    "wgmma.mma_async.sync.aligned.m64n128k16.f32.bf16.bf16 "
    "{%0, %1, %2, %3, %4, %5, %6, %7, %8, %9, %10, %11, %12, %13, %14, %15, "
    "%16, %17, %18, %19, %20, %21, %22, %23, %24, %25, %26, %27, %28, %29, %30, %31, "
    "%32, %33, %34, %35, %36, %37, %38, %39, %40, %41, %42, %43, %44, %45, %46, %47, "
    "%48, %49, %50, %51, %52, %53, %54, %55, %56, %57, %58, %59, %60, %61, %62, %63}, "
    "da, db, 0, 1, 1, %70, %71;\n}\n"
    : "+f"(d[0]), "+f"(d[1]), "+f"(d[2]), "+f"(d[3]), "+f"(d[4]), "+f"(d[5]), "+f"(d[6]), "+f"(d[7]),
      "+f"(d[8]), "+f"(d[9]), "+f"(d[10]), "+f"(d[11]), "+f"(d[12]), "+f"(d[13]), "+f"(d[14]), "+f"(d[15]),
      "+f"(d[16]), "+f"(d[17]), "+f"(d[18]), "+f"(d[19]), "+f"(d[20]), "+f"(d[21]), "+f"(d[22]), "+f"(d[23]),
      "+f"(d[24]), "+f"(d[25]), "+f"(d[26]), "+f"(d[27]), "+f"(d[28]), "+f"(d[29]), "+f"(d[30]), "+f"(d[31]),
      "+f"(d[32]), "+f"(d[33]), "+f"(d[34]), "+f"(d[35]), "+f"(d[36]), "+f"(d[37]), "+f"(d[38]), "+f"(d[39]),
      "+f"(d[40]), "+f"(d[41]), "+f"(d[42]), "+f"(d[43]), "+f"(d[44]), "+f"(d[45]), "+f"(d[46]), "+f"(d[47]),
      "+f"(d[48]), "+f"(d[49]), "+f"(d[50]), "+f"(d[51]), "+f"(d[52]), "+f"(d[53]), "+f"(d[54]), "+f"(d[55]),
      "+f"(d[56]), "+f"(d[57]), "+f"(d[58]), "+f"(d[59]), "+f"(d[60]), "+f"(d[61]), "+f"(d[62]), "+f"(d[63])
    : "r"(alo), "r"(blo), "n"(AOFF >> 4), "n"(BOFF >> 4), "n"(BHI), "n"(AHI), "n"(TA), "n"(TB));
  } else {
  asm volatile("{\n.reg .b32 ta, tb;\n.reg .b64 da, db;\n"
    "add.u32 ta, %64, %66;\nmov.b64 da, {ta, %69};\n"
    "add.u32 tb, %65, %67;\nmov.b64 db, {tb, %68};\n"
    "wgmma.mma_async.sync.aligned.m64n128k16.f32.bf16.bf16 "
    "{%0, %1, %2, %3, %4, %5, %6, %7, %8, %9, %10, %11, %12, %13, %14, %15, "
    "%16, %17, %18, %19, %20, %21, %22, %23, %24, %25, %26, %27, %28, %29, %30, %31, "
    "%32, %33, %34, %35, %36, %37, %38, %39, %40, %41, %42, %43, %44, %45, %46, %47, "
    "%48, %49, %50, %51, %52, %53, %54, %55, %56, %57, %58, %59, %60, %61, %62, %63}, "
    "da, db, 0, 1, 1, %70, %71;\n}\n"
    : "=f"(d[0]), "=f"(d[1]), "=f"(d[2]), "=f"(d[3]), "=f"(d[4]), "=f"(d[5]), "=f"(d[6]), "=f"(d[7]),
      "=f"(d[8]), "=f"(d[9]), "=f"(d[10]), "=f"(d[11]), "=f"(d[12]), "=f"(d[13]), "=f"(d[14]), "=f"(d[15]),
      "=f"(d[16]), "=f"(d[17]), "=f"(d[18]), "=f"(d[19]), "=f"(d[20]), "=f"(d[21]), "=f"(d[22]), "=f"(d[23]),
      "=f"(d[24]), "=f"(d[25]), "=f"(d[26]), "=f"(d[27]), "=f"(d[28]), "=f"(d[29]), "=f"(d[30]), "=f"(d[31]),
      "=f"(d[32]), "=f"(d[33]), "=f"(d[34]), "=f"(d[35]), "=f"(d[36]), "=f"(d[37]), "=f"(d[38]), "=f"(d[39]),
      "=f"(d[40]), "=f"(d[41]), "=f"(d[42]), "=f"(d[43]), "=f"(d[44]), "=f"(d[45]), "=f"(d[46]), "=f"(d[47]),
      "=f"(d[48]), "=f"(d[49]), "=f"(d[50]), "=f"(d[51]), "=f"(d[52]), "=f"(d[53]), "=f"(d[54]), "=f"(d[55]),
      "=f"(d[56]), "=f"(d[57]), "=f"(d[58]), "=f"(d[59]), "=f"(d[60]), "=f"(d[61]), "=f"(d[62]), "=f"(d[63])
    : "r"(alo), "r"(blo), "n"(AOFF >> 4), "n"(BOFF >> 4), "n"(BHI), "n"(AHI), "n"(TA), "n"(TB));
  }
}
template <int AOFF, int BOFF, int SCALE, unsigned BHI = 0x40000040u, unsigned AHI = 0x40000040u, int TA = 0, int TB = 1>
__device__ __forceinline__ void wgmma_ss_n112(float* d, uint32_t alo, uint32_t blo) {
  if constexpr (SCALE == 1) {
  asm volatile("{\n.reg .b32 ta, tb;\n.reg .b64 da, db;\n"
    "add.u32 ta, %56, %58;\nmov.b64 da, {ta, %61};\n"
    "add.u32 tb, %57, %59;\nmov.b64 db, {tb, %60};\n"
    "wgmma.mma_async.sync.aligned.m64n112k16.f32.bf16.bf16 "
    "{%0, %1, %2, %3, %4, %5, %6, %7, %8, %9, %10, %11, %12, %13, %14, %15, "
    "%16, %17, %18, %19, %20, %21, %22, %23, %24, %25, %26, %27, %28, %29, %30, %31, "
    "%32, %33, %34, %35, %36, %37, %38, %39, %40, %41, %42, %43, %44, %45, %46, %47, "
    "%48, %49, %50, %51, %52, %53, %54, %55}, "
    "da, db, 1, 1, 1, %62, %63;\n}\n"
    : "+f"(d[0]), "+f"(d[1]), "+f"(d[2]), "+f"(d[3]), "+f"(d[4]), "+f"(d[5]), "+f"(d[6]), "+f"(d[7]),
      "+f"(d[8]), "+f"(d[9]), "+f"(d[10]), "+f"(d[11]), "+f"(d[12]), "+f"(d[13]), "+f"(d[14]), "+f"(d[15]),
      "+f"(d[16]), "+f"(d[17]), "+f"(d[18]), "+f"(d[19]), "+f"(d[20]), "+f"(d[21]), "+f"(d[22]), "+f"(d[23]),
      "+f"(d[24]), "+f"(d[25]), "+f"(d[26]), "+f"(d[27]), "+f"(d[28]), "+f"(d[29]), "+f"(d[30]), "+f"(d[31]),
      "+f"(d[32]), "+f"(d[33]), "+f"(d[34]), "+f"(d[35]), "+f"(d[36]), "+f"(d[37]), "+f"(d[38]), "+f"(d[39]),
      "+f"(d[40]), "+f"(d[41]), "+f"(d[42]), "+f"(d[43]), "+f"(d[44]), "+f"(d[45]), "+f"(d[46]), "+f"(d[47]),
      "+f"(d[48]), "+f"(d[49]), "+f"(d[50]), "+f"(d[51]), "+f"(d[52]), "+f"(d[53]), "+f"(d[54]), "+f"(d[55])
    : "r"(alo), "r"(blo), "n"(AOFF >> 4), "n"(BOFF >> 4), "n"(BHI), "n"(AHI), "n"(TA), "n"(TB));
  } else if constexpr (SCALE == 0) {
  asm volatile("{\n.reg .b32 ta, tb;\n.reg .b64 da, db;\n"
    "add.u32 ta, %56, %58;\nmov.b64 da, {ta, %61};\n"
    "add.u32 tb, %57, %59;\nmov.b64 db, {tb, %60};\n"
    "wgmma.mma_async.sync.aligned.m64n112k16.f32.bf16.bf16 "
    "{%0, %1, %2, %3, %4, %5, %6, %7, %8, %9, %10, %11, %12, %13, %14, %15, "
    "%16, %17, %18, %19, %20, %21, %22, %23, %24, %25, %26, %27, %28, %29, %30, %31, "
    "%32, %33, %34, %35, %36, %37, %38, %39, %40, %41, %42, %43, %44, %45, %46, %47, "
    "%48, %49, %50, %51, %52, %53, %54, %55}, "
    "da, db, 0, 1, 1, %62, %63;\n}\n"
    : "+f"(d[0]), "+f"(d[1]), "+f"(d[2]), "+f"(d[3]), "+f"(d[4]), "+f"(d[5]), "+f"(d[6]), "+f"(d[7]),
      "+f"(d[8]), "+f"(d[9]), "+f"(d[10]), "+f"(d[11]), "+f"(d[12]), "+f"(d[13]), "+f"(d[14]), "+f"(d[15]),
      "+f"(d[16]), "+f"(d[17]), "+f"(d[18]), "+f"(d[19]), "+f"(d[20]), "+f"(d[21]), "+f"(d[22]), "+f"(d[23]),
      "+f"(d[24]), "+f"(d[25]), "+f"(d[26]), "+f"(d[27]), "+f"(d[28]), "+f"(d[29]), "+f"(d[30]), "+f"(d[31]),
      "+f"(d[32]), "+f"(d[33]), "+f"(d[34]), "+f"(d[35]), "+f"(d[36]), "+f"(d[37]), "+f"(d[38]), "+f"(d[39]),
      "+f"(d[40]), "+f"(d[41]), "+f"(d[42]), "+f"(d[43]), "+f"(d[44]), "+f"(d[45]), "+f"(d[46]), "+f"(d[47]),
      "+f"(d[48]), "+f"(d[49]), "+f"(d[50]), "+f"(d[51]), "+f"(d[52]), "+f"(d[53]), "+f"(d[54]), "+f"(d[55])
    : "r"(alo), "r"(blo), "n"(AOFF >> 4), "n"(BOFF >> 4), "n"(BHI), "n"(AHI), "n"(TA), "n"(TB));
  } else {
  asm volatile("{\n.reg .b32 ta, tb;\n.reg .b64 da, db;\n"
    "add.u32 ta, %56, %58;\nmov.b64 da, {ta, %61};\n"
    "add.u32 tb, %57, %59;\nmov.b64 db, {tb, %60};\n"
    "wgmma.mma_async.sync.aligned.m64n112k16.f32.bf16.bf16 "
    "{%0, %1, %2, %3, %4, %5, %6, %7, %8, %9, %10, %11, %12, %13, %14, %15, "
    "%16, %17, %18, %19, %20, %21, %22, %23, %24, %25, %26, %27, %28, %29, %30, %31, "
    "%32, %33, %34, %35, %36, %37, %38, %39, %40, %41, %42, %43, %44, %45, %46, %47, "
    "%48, %49, %50, %51, %52, %53, %54, %55}, "
    "da, db, 0, 1, 1, %62, %63;\n}\n"
    : "=f"(d[0]), "=f"(d[1]), "=f"(d[2]), "=f"(d[3]), "=f"(d[4]), "=f"(d[5]), "=f"(d[6]), "=f"(d[7]),
      "=f"(d[8]), "=f"(d[9]), "=f"(d[10]), "=f"(d[11]), "=f"(d[12]), "=f"(d[13]), "=f"(d[14]), "=f"(d[15]),
      "=f"(d[16]), "=f"(d[17]), "=f"(d[18]), "=f"(d[19]), "=f"(d[20]), "=f"(d[21]), "=f"(d[22]), "=f"(d[23]),
      "=f"(d[24]), "=f"(d[25]), "=f"(d[26]), "=f"(d[27]), "=f"(d[28]), "=f"(d[29]), "=f"(d[30]), "=f"(d[31]),
      "=f"(d[32]), "=f"(d[33]), "=f"(d[34]), "=f"(d[35]), "=f"(d[36]), "=f"(d[37]), "=f"(d[38]), "=f"(d[39]),
      "=f"(d[40]), "=f"(d[41]), "=f"(d[42]), "=f"(d[43]), "=f"(d[44]), "=f"(d[45]), "=f"(d[46]), "=f"(d[47]),
      "=f"(d[48]), "=f"(d[49]), "=f"(d[50]), "=f"(d[51]), "=f"(d[52]), "=f"(d[53]), "=f"(d[54]), "=f"(d[55])
    : "r"(alo), "r"(blo), "n"(AOFF >> 4), "n"(BOFF >> 4), "n"(BHI), "n"(AHI), "n"(TA), "n"(TB));
  }
}
template <int AOFF, int BOFF, int SCALE, unsigned BHI = 0x40000040u, unsigned AHI = 0x40000040u, int TA = 0, int TB = 1>
__device__ __forceinline__ void wgmma_ss_n32(float* d, uint32_t alo, uint32_t blo) {
  if constexpr (SCALE == 1) {
  asm volatile("{\n.reg .b32 ta, tb;\n.reg .b64 da, db;\n"
    "add.u32 ta, %16, %18;\nmov.b64 da, {ta, %21};\n"
    "add.u32 tb, %17, %19;\nmov.b64 db, {tb, %20};\n"
    "wgmma.mma_async.sync.aligned.m64n32k16.f32.bf16.bf16 "
    "{%0, %1, %2, %3, %4, %5, %6, %7, %8, %9, %10, %11, %12, %13, %14, %15}, "
    "da, db, 1, 1, 1, %22, %23;\n}\n"
    : "+f"(d[0]), "+f"(d[1]), "+f"(d[2]), "+f"(d[3]), "+f"(d[4]), "+f"(d[5]), "+f"(d[6]), "+f"(d[7]),
      "+f"(d[8]), "+f"(d[9]), "+f"(d[10]), "+f"(d[11]), "+f"(d[12]), "+f"(d[13]), "+f"(d[14]), "+f"(d[15])
    : "r"(alo), "r"(blo), "n"(AOFF >> 4), "n"(BOFF >> 4), "n"(BHI), "n"(AHI), "n"(TA), "n"(TB));
  } else if constexpr (SCALE == 0) {
  asm volatile("{\n.reg .b32 ta, tb;\n.reg .b64 da, db;\n"
    "add.u32 ta, %16, %18;\nmov.b64 da, {ta, %21};\n"
    "add.u32 tb, %17, %19;\nmov.b64 db, {tb, %20};\n"
    "wgmma.mma_async.sync.aligned.m64n32k16.f32.bf16.bf16 "
    "{%0, %1, %2, %3, %4, %5, %6, %7, %8, %9, %10, %11, %12, %13, %14, %15}, "
    "da, db, 0, 1, 1, %22, %23;\n}\n"
    : "+f"(d[0]), "+f"(d[1]), "+f"(d[2]), "+f"(d[3]), "+f"(d[4]), "+f"(d[5]), "+f"(d[6]), "+f"(d[7]),
      "+f"(d[8]), "+f"(d[9]), "+f"(d[10]), "+f"(d[11]), "+f"(d[12]), "+f"(d[13]), "+f"(d[14]), "+f"(d[15])
    : "r"(alo), "r"(blo), "n"(AOFF >> 4), "n"(BOFF >> 4), "n"(BHI), "n"(AHI), "n"(TA), "n"(TB));
  } else {
  asm volatile("{\n.reg .b32 ta, tb;\n.reg .b64 da, db;\n"
    "add.u32 ta, %16, %18;\nmov.b64 da, {ta, %21};\n"
    "add.u32 tb, %17, %19;\nmov.b64 db, {tb, %20};\n"
    "wgmma.mma_async.sync.aligned.m64n32k16.f32.bf16.bf16 "
    "{%0, %1, %2, %3, %4, %5, %6, %7, %8, %9, %10, %11, %12, %13, %14, %15}, "
    "da, db, 0, 1, 1, %22, %23;\n}\n"
    : "=f"(d[0]), "=f"(d[1]), "=f"(d[2]), "=f"(d[3]), "=f"(d[4]), "=f"(d[5]), "=f"(d[6]), "=f"(d[7]),
      "=f"(d[8]), "=f"(d[9]), "=f"(d[10]), "=f"(d[11]), "=f"(d[12]), "=f"(d[13]), "=f"(d[14]), "=f"(d[15])
    : "r"(alo), "r"(blo), "n"(AOFF >> 4), "n"(BOFF >> 4), "n"(BHI), "n"(AHI), "n"(TA), "n"(TB));
  }
}
template <int AOFF, int BOFF, int SCALE, unsigned BHI = 0x40000040u, unsigned AHI = 0x40000040u, int TA = 0, int TB = 1>
__device__ __forceinline__ void wgmma_ss_n8(float* d, uint32_t alo, uint32_t blo) {
  if constexpr (SCALE == 1) {
  asm volatile("{\n.reg .b32 ta, tb;\n.reg .b64 da, db;\n"
    "add.u32 ta, %4, %6;\nmov.b64 da, {ta, %9};\n"
    "add.u32 tb, %5, %7;\nmov.b64 db, {tb, %8};\n"
    "wgmma.mma_async.sync.aligned.m64n8k16.f32.bf16.bf16 "
    "{%0, %1, %2, %3}, "
    "da, db, 1, 1, 1, %10, %11;\n}\n"
    : "+f"(d[0]), "+f"(d[1]), "+f"(d[2]), "+f"(d[3])
    : "r"(alo), "r"(blo), "n"(AOFF >> 4), "n"(BOFF >> 4), "n"(BHI), "n"(AHI), "n"(TA), "n"(TB));
  } else if constexpr (SCALE == 0) {
  asm volatile("{\n.reg .b32 ta, tb;\n.reg .b64 da, db;\n"
    "add.u32 ta, %4, %6;\nmov.b64 da, {ta, %9};\n"
    "add.u32 tb, %5, %7;\nmov.b64 db, {tb, %8};\n"
    "wgmma.mma_async.sync.aligned.m64n8k16.f32.bf16.bf16 "
    "{%0, %1, %2, %3}, "
    "da, db, 0, 1, 1, %10, %11;\n}\n"
    : "+f"(d[0]), "+f"(d[1]), "+f"(d[2]), "+f"(d[3])
    : "r"(alo), "r"(blo), "n"(AOFF >> 4), "n"(BOFF >> 4), "n"(BHI), "n"(AHI), "n"(TA), "n"(TB));
  } else {
  asm volatile("{\n.reg .b32 ta, tb;\n.reg .b64 da, db;\n"
    "add.u32 ta, %4, %6;\nmov.b64 da, {ta, %9};\n"
    "add.u32 tb, %5, %7;\nmov.b64 db, {tb, %8};\n"
    "wgmma.mma_async.sync.aligned.m64n8k16.f32.bf16.bf16 "
    "{%0, %1, %2, %3}, "
    "da, db, 0, 1, 1, %10, %11;\n}\n"
    : "=f"(d[0]), "=f"(d[1]), "=f"(d[2]), "=f"(d[3])
    : "r"(alo), "r"(blo), "n"(AOFF >> 4), "n"(BOFF >> 4), "n"(BHI), "n"(AHI), "n"(TA), "n"(TB));
  }
}
template <int BOFF, int SCALE, unsigned BHI = 0x40000040u, int TB = 1>
__device__ __forceinline__ void wgmma_rs_n192(float* d, const uint32_t (&a)[4], uint32_t blo) {
  if constexpr (SCALE == 1) {
  asm volatile("{\n.reg .b32 tb;\n.reg .b64 db;\n"
    "add.u32 tb, %100, %101;\nmov.b64 db, {tb, %102};\n"
    "wgmma.mma_async.sync.aligned.m64n192k16.f32.bf16.bf16 "
    "{%0, %1, %2, %3, %4, %5, %6, %7, %8, %9, %10, %11, %12, %13, %14, %15, "
    "%16, %17, %18, %19, %20, %21, %22, %23, %24, %25, %26, %27, %28, %29, %30, %31, "
    "%32, %33, %34, %35, %36, %37, %38, %39, %40, %41, %42, %43, %44, %45, %46, %47, "
    "%48, %49, %50, %51, %52, %53, %54, %55, %56, %57, %58, %59, %60, %61, %62, %63, "
    "%64, %65, %66, %67, %68, %69, %70, %71, %72, %73, %74, %75, %76, %77, %78, %79, "
    "%80, %81, %82, %83, %84, %85, %86, %87, %88, %89, %90, %91, %92, %93, %94, %95}, "
    "{%96, %97, %98, %99}, db, 1, 1, 1, %103;\n}\n"
    : "+f"(d[0]), "+f"(d[1]), "+f"(d[2]), "+f"(d[3]), "+f"(d[4]), "+f"(d[5]), "+f"(d[6]), "+f"(d[7]),
      "+f"(d[8]), "+f"(d[9]), "+f"(d[10]), "+f"(d[11]), "+f"(d[12]), "+f"(d[13]), "+f"(d[14]), "+f"(d[15]),
      "+f"(d[16]), "+f"(d[17]), "+f"(d[18]), "+f"(d[19]), "+f"(d[20]), "+f"(d[21]), "+f"(d[22]), "+f"(d[23]),
      "+f"(d[24]), "+f"(d[25]), "+f"(d[26]), "+f"(d[27]), "+f"(d[28]), "+f"(d[29]), "+f"(d[30]), "+f"(d[31]),
      "+f"(d[32]), "+f"(d[33]), "+f"(d[34]), "+f"(d[35]), "+f"(d[36]), "+f"(d[37]), "+f"(d[38]), "+f"(d[39]),
      "+f"(d[40]), "+f"(d[41]), "+f"(d[42]), "+f"(d[43]), "+f"(d[44]), "+f"(d[45]), "+f"(d[46]), "+f"(d[47]),
      "+f"(d[48]), "+f"(d[49]), "+f"(d[50]), "+f"(d[51]), "+f"(d[52]), "+f"(d[53]), "+f"(d[54]), "+f"(d[55]),
      "+f"(d[56]), "+f"(d[57]), "+f"(d[58]), "+f"(d[59]), "+f"(d[60]), "+f"(d[61]), "+f"(d[62]), "+f"(d[63]),
      "+f"(d[64]), "+f"(d[65]), "+f"(d[66]), "+f"(d[67]), "+f"(d[68]), "+f"(d[69]), "+f"(d[70]), "+f"(d[71]),
      "+f"(d[72]), "+f"(d[73]), "+f"(d[74]), "+f"(d[75]), "+f"(d[76]), "+f"(d[77]), "+f"(d[78]), "+f"(d[79]),
      "+f"(d[80]), "+f"(d[81]), "+f"(d[82]), "+f"(d[83]), "+f"(d[84]), "+f"(d[85]), "+f"(d[86]), "+f"(d[87]),
      "+f"(d[88]), "+f"(d[89]), "+f"(d[90]), "+f"(d[91]), "+f"(d[92]), "+f"(d[93]), "+f"(d[94]), "+f"(d[95])
    : "r"(a[0]), "r"(a[1]), "r"(a[2]), "r"(a[3]), "r"(blo), "n"(BOFF >> 4), "n"(BHI), "n"(TB));
  } else if constexpr (SCALE == 0) {
  asm volatile("{\n.reg .b32 tb;\n.reg .b64 db;\n"
    "add.u32 tb, %100, %101;\nmov.b64 db, {tb, %102};\n"
    "wgmma.mma_async.sync.aligned.m64n192k16.f32.bf16.bf16 "
    "{%0, %1, %2, %3, %4, %5, %6, %7, %8, %9, %10, %11, %12, %13, %14, %15, "
    "%16, %17, %18, %19, %20, %21, %22, %23, %24, %25, %26, %27, %28, %29, %30, %31, "
    "%32, %33, %34, %35, %36, %37, %38, %39, %40, %41, %42, %43, %44, %45, %46, %47, "
    "%48, %49, %50, %51, %52, %53, %54, %55, %56, %57, %58, %59, %60, %61, %62, %63, "
    "%64, %65, %66, %67, %68, %69, %70, %71, %72, %73, %74, %75, %76, %77, %78, %79, "
    "%80, %81, %82, %83, %84, %85, %86, %87, %88, %89, %90, %91, %92, %93, %94, %95}, "
    "{%96, %97, %98, %99}, db, 0, 1, 1, %103;\n}\n"
    : "+f"(d[0]), "+f"(d[1]), "+f"(d[2]), "+f"(d[3]), "+f"(d[4]), "+f"(d[5]), "+f"(d[6]), "+f"(d[7]),
      "+f"(d[8]), "+f"(d[9]), "+f"(d[10]), "+f"(d[11]), "+f"(d[12]), "+f"(d[13]), "+f"(d[14]), "+f"(d[15]),
      "+f"(d[16]), "+f"(d[17]), "+f"(d[18]), "+f"(d[19]), "+f"(d[20]), "+f"(d[21]), "+f"(d[22]), "+f"(d[23]),
      "+f"(d[24]), "+f"(d[25]), "+f"(d[26]), "+f"(d[27]), "+f"(d[28]), "+f"(d[29]), "+f"(d[30]), "+f"(d[31]),
      "+f"(d[32]), "+f"(d[33]), "+f"(d[34]), "+f"(d[35]), "+f"(d[36]), "+f"(d[37]), "+f"(d[38]), "+f"(d[39]),
      "+f"(d[40]), "+f"(d[41]), "+f"(d[42]), "+f"(d[43]), "+f"(d[44]), "+f"(d[45]), "+f"(d[46]), "+f"(d[47]),
      "+f"(d[48]), "+f"(d[49]), "+f"(d[50]), "+f"(d[51]), "+f"(d[52]), "+f"(d[53]), "+f"(d[54]), "+f"(d[55]),
      "+f"(d[56]), "+f"(d[57]), "+f"(d[58]), "+f"(d[59]), "+f"(d[60]), "+f"(d[61]), "+f"(d[62]), "+f"(d[63]),
      "+f"(d[64]), "+f"(d[65]), "+f"(d[66]), "+f"(d[67]), "+f"(d[68]), "+f"(d[69]), "+f"(d[70]), "+f"(d[71]),
      "+f"(d[72]), "+f"(d[73]), "+f"(d[74]), "+f"(d[75]), "+f"(d[76]), "+f"(d[77]), "+f"(d[78]), "+f"(d[79]),
      "+f"(d[80]), "+f"(d[81]), "+f"(d[82]), "+f"(d[83]), "+f"(d[84]), "+f"(d[85]), "+f"(d[86]), "+f"(d[87]),
      "+f"(d[88]), "+f"(d[89]), "+f"(d[90]), "+f"(d[91]), "+f"(d[92]), "+f"(d[93]), "+f"(d[94]), "+f"(d[95])
    : "r"(a[0]), "r"(a[1]), "r"(a[2]), "r"(a[3]), "r"(blo), "n"(BOFF >> 4), "n"(BHI), "n"(TB));
  } else {
  asm volatile("{\n.reg .b32 tb;\n.reg .b64 db;\n"
    "add.u32 tb, %100, %101;\nmov.b64 db, {tb, %102};\n"
    "wgmma.mma_async.sync.aligned.m64n192k16.f32.bf16.bf16 "
    "{%0, %1, %2, %3, %4, %5, %6, %7, %8, %9, %10, %11, %12, %13, %14, %15, "
    "%16, %17, %18, %19, %20, %21, %22, %23, %24, %25, %26, %27, %28, %29, %30, %31, "
    "%32, %33, %34, %35, %36, %37, %38, %39, %40, %41, %42, %43, %44, %45, %46, %47, "
    "%48, %49, %50, %51, %52, %53, %54, %55, %56, %57, %58, %59, %60, %61, %62, %63, "
    "%64, %65, %66, %67, %68, %69, %70, %71, %72, %73, %74, %75, %76, %77, %78, %79, "
    "%80, %81, %82, %83, %84, %85, %86, %87, %88, %89, %90, %91, %92, %93, %94, %95}, "
    "{%96, %97, %98, %99}, db, 0, 1, 1, %103;\n}\n"
    : "=f"(d[0]), "=f"(d[1]), "=f"(d[2]), "=f"(d[3]), "=f"(d[4]), "=f"(d[5]), "=f"(d[6]), "=f"(d[7]),
      "=f"(d[8]), "=f"(d[9]), "=f"(d[10]), "=f"(d[11]), "=f"(d[12]), "=f"(d[13]), "=f"(d[14]), "=f"(d[15]),
      "=f"(d[16]), "=f"(d[17]), "=f"(d[18]), "=f"(d[19]), "=f"(d[20]), "=f"(d[21]), "=f"(d[22]), "=f"(d[23]),
      "=f"(d[24]), "=f"(d[25]), "=f"(d[26]), "=f"(d[27]), "=f"(d[28]), "=f"(d[29]), "=f"(d[30]), "=f"(d[31]),
      "=f"(d[32]), "=f"(d[33]), "=f"(d[34]), "=f"(d[35]), "=f"(d[36]), "=f"(d[37]), "=f"(d[38]), "=f"(d[39]),
      "=f"(d[40]), "=f"(d[41]), "=f"(d[42]), "=f"(d[43]), "=f"(d[44]), "=f"(d[45]), "=f"(d[46]), "=f"(d[47]),
      "=f"(d[48]), "=f"(d[49]), "=f"(d[50]), "=f"(d[51]), "=f"(d[52]), "=f"(d[53]), "=f"(d[54]), "=f"(d[55]),
      "=f"(d[56]), "=f"(d[57]), "=f"(d[58]), "=f"(d[59]), "=f"(d[60]), "=f"(d[61]), "=f"(d[62]), "=f"(d[63]),
      "=f"(d[64]), "=f"(d[65]), "=f"(d[66]), "=f"(d[67]), "=f"(d[68]), "=f"(d[69]), "=f"(d[70]), "=f"(d[71]),
      "=f"(d[72]), "=f"(d[73]), "=f"(d[74]), "=f"(d[75]), "=f"(d[76]), "=f"(d[77]), "=f"(d[78]), "=f"(d[79]),
      "=f"(d[80]), "=f"(d[81]), "=f"(d[82]), "=f"(d[83]), "=f"(d[84]), "=f"(d[85]), "=f"(d[86]), "=f"(d[87]),
      "=f"(d[88]), "=f"(d[89]), "=f"(d[90]), "=f"(d[91]), "=f"(d[92]), "=f"(d[93]), "=f"(d[94]), "=f"(d[95])
    : "r"(a[0]), "r"(a[1]), "r"(a[2]), "r"(a[3]), "r"(blo), "n"(BOFF >> 4), "n"(BHI), "n"(TB));
  }
}
template <int BOFF, int SCALE, unsigned BHI = 0x40000040u, int TB = 1>
__device__ __forceinline__ void wgmma_rs_n128(float* d, const uint32_t (&a)[4], uint32_t blo) {
  if constexpr (SCALE == 1) {
  asm volatile("{\n.reg .b32 tb;\n.reg .b64 db;\n"
    "add.u32 tb, %68, %69;\nmov.b64 db, {tb, %70};\n"
    "wgmma.mma_async.sync.aligned.m64n128k16.f32.bf16.bf16 "
    "{%0, %1, %2, %3, %4, %5, %6, %7, %8, %9, %10, %11, %12, %13, %14, %15, "
    "%16, %17, %18, %19, %20, %21, %22, %23, %24, %25, %26, %27, %28, %29, %30, %31, "
    "%32, %33, %34, %35, %36, %37, %38, %39, %40, %41, %42, %43, %44, %45, %46, %47, "
    "%48, %49, %50, %51, %52, %53, %54, %55, %56, %57, %58, %59, %60, %61, %62, %63}, "
    "{%64, %65, %66, %67}, db, 1, 1, 1, %71;\n}\n"
    : "+f"(d[0]), "+f"(d[1]), "+f"(d[2]), "+f"(d[3]), "+f"(d[4]), "+f"(d[5]), "+f"(d[6]), "+f"(d[7]),
      "+f"(d[8]), "+f"(d[9]), "+f"(d[10]), "+f"(d[11]), "+f"(d[12]), "+f"(d[13]), "+f"(d[14]), "+f"(d[15]),
      "+f"(d[16]), "+f"(d[17]), "+f"(d[18]), "+f"(d[19]), "+f"(d[20]), "+f"(d[21]), "+f"(d[22]), "+f"(d[23]),
      "+f"(d[24]), "+f"(d[25]), "+f"(d[26]), "+f"(d[27]), "+f"(d[28]), "+f"(d[29]), "+f"(d[30]), "+f"(d[31]),
      "+f"(d[32]), "+f"(d[33]), "+f"(d[34]), "+f"(d[35]), "+f"(d[36]), "+f"(d[37]), "+f"(d[38]), "+f"(d[39]),
      "+f"(d[40]), "+f"(d[41]), "+f"(d[42]), "+f"(d[43]), "+f"(d[44]), "+f"(d[45]), "+f"(d[46]), "+f"(d[47]),
      "+f"(d[48]), "+f"(d[49]), "+f"(d[50]), "+f"(d[51]), "+f"(d[52]), "+f"(d[53]), "+f"(d[54]), "+f"(d[55]),
      "+f"(d[56]), "+f"(d[57]), "+f"(d[58]), "+f"(d[59]), "+f"(d[60]), "+f"(d[61]), "+f"(d[62]), "+f"(d[63])
    : "r"(a[0]), "r"(a[1]), "r"(a[2]), "r"(a[3]), "r"(blo), "n"(BOFF >> 4), "n"(BHI), "n"(TB));
  } else if constexpr (SCALE == 0) {
  asm volatile("{\n.reg .b32 tb;\n.reg .b64 db;\n"
    "add.u32 tb, %68, %69;\nmov.b64 db, {tb, %70};\n"
    "wgmma.mma_async.sync.aligned.m64n128k16.f32.bf16.bf16 "
    "{%0, %1, %2, %3, %4, %5, %6, %7, %8, %9, %10, %11, %12, %13, %14, %15, "
    "%16, %17, %18, %19, %20, %21, %22, %23, %24, %25, %26, %27, %28, %29, %30, %31, "
    "%32, %33, %34, %35, %36, %37, %38, %39, %40, %41, %42, %43, %44, %45, %46, %47, "
    "%48, %49, %50, %51, %52, %53, %54, %55, %56, %57, %58, %59, %60, %61, %62, %63}, "
    "{%64, %65, %66, %67}, db, 0, 1, 1, %71;\n}\n"
    : "+f"(d[0]), "+f"(d[1]), "+f"(d[2]), "+f"(d[3]), "+f"(d[4]), "+f"(d[5]), "+f"(d[6]), "+f"(d[7]),
      "+f"(d[8]), "+f"(d[9]), "+f"(d[10]), "+f"(d[11]), "+f"(d[12]), "+f"(d[13]), "+f"(d[14]), "+f"(d[15]),
      "+f"(d[16]), "+f"(d[17]), "+f"(d[18]), "+f"(d[19]), "+f"(d[20]), "+f"(d[21]), "+f"(d[22]), "+f"(d[23]),
      "+f"(d[24]), "+f"(d[25]), "+f"(d[26]), "+f"(d[27]), "+f"(d[28]), "+f"(d[29]), "+f"(d[30]), "+f"(d[31]),
      "+f"(d[32]), "+f"(d[33]), "+f"(d[34]), "+f"(d[35]), "+f"(d[36]), "+f"(d[37]), "+f"(d[38]), "+f"(d[39]),
      "+f"(d[40]), "+f"(d[41]), "+f"(d[42]), "+f"(d[43]), "+f"(d[44]), "+f"(d[45]), "+f"(d[46]), "+f"(d[47]),
      "+f"(d[48]), "+f"(d[49]), "+f"(d[50]), "+f"(d[51]), "+f"(d[52]), "+f"(d[53]), "+f"(d[54]), "+f"(d[55]),
      "+f"(d[56]), "+f"(d[57]), "+f"(d[58]), "+f"(d[59]), "+f"(d[60]), "+f"(d[61]), "+f"(d[62]), "+f"(d[63])
    : "r"(a[0]), "r"(a[1]), "r"(a[2]), "r"(a[3]), "r"(blo), "n"(BOFF >> 4), "n"(BHI), "n"(TB));
  } else {
  asm volatile("{\n.reg .b32 tb;\n.reg .b64 db;\n"
    "add.u32 tb, %68, %69;\nmov.b64 db, {tb, %70};\n"
    "wgmma.mma_async.sync.aligned.m64n128k16.f32.bf16.bf16 "
    "{%0, %1, %2, %3, %4, %5, %6, %7, %8, %9, %10, %11, %12, %13, %14, %15, "
    "%16, %17, %18, %19, %20, %21, %22, %23, %24, %25, %26, %27, %28, %29, %30, %31, "
    "%32, %33, %34, %35, %36, %37, %38, %39, %40, %41, %42, %43, %44, %45, %46, %47, "
    "%48, %49, %50, %51, %52, %53, %54, %55, %56, %57, %58, %59, %60, %61, %62, %63}, "
    "{%64, %65, %66, %67}, db, 0, 1, 1, %71;\n}\n"
    : "=f"(d[0]), "=f"(d[1]), "=f"(d[2]), "=f"(d[3]), "=f"(d[4]), "=f"(d[5]), "=f"(d[6]), "=f"(d[7]),
      "=f"(d[8]), "=f"(d[9]), "=f"(d[10]), "=f"(d[11]), "=f"(d[12]), "=f"(d[13]), "=f"(d[14]), "=f"(d[15]),
      "=f"(d[16]), "=f"(d[17]), "=f"(d[18]), "=f"(d[19]), "=f"(d[20]), "=f"(d[21]), "=f"(d[22]), "=f"(d[23]),
      "=f"(d[24]), "=f"(d[25]), "=f"(d[26]), "=f"(d[27]), "=f"(d[28]), "=f"(d[29]), "=f"(d[30]), "=f"(d[31]),
      "=f"(d[32]), "=f"(d[33]), "=f"(d[34]), "=f"(d[35]), "=f"(d[36]), "=f"(d[37]), "=f"(d[38]), "=f"(d[39]),
      "=f"(d[40]), "=f"(d[41]), "=f"(d[42]), "=f"(d[43]), "=f"(d[44]), "=f"(d[45]), "=f"(d[46]), "=f"(d[47]),
      "=f"(d[48]), "=f"(d[49]), "=f"(d[50]), "=f"(d[51]), "=f"(d[52]), "=f"(d[53]), "=f"(d[54]), "=f"(d[55]),
      "=f"(d[56]), "=f"(d[57]), "=f"(d[58]), "=f"(d[59]), "=f"(d[60]), "=f"(d[61]), "=f"(d[62]), "=f"(d[63])
    : "r"(a[0]), "r"(a[1]), "r"(a[2]), "r"(a[3]), "r"(blo), "n"(BOFF >> 4), "n"(BHI), "n"(TB));
  }
}
template <int BOFF, int SCALE, unsigned BHI = 0x40000040u, int TB = 1>
__device__ __forceinline__ void wgmma_rs_n64(float* d, const uint32_t (&a)[4], uint32_t blo) {
  if constexpr (SCALE == 1) {
  asm volatile("{\n.reg .b32 tb;\n.reg .b64 db;\n"
    "add.u32 tb, %36, %37;\nmov.b64 db, {tb, %38};\n"
    "wgmma.mma_async.sync.aligned.m64n64k16.f32.bf16.bf16 "
    "{%0, %1, %2, %3, %4, %5, %6, %7, %8, %9, %10, %11, %12, %13, %14, %15, "
    "%16, %17, %18, %19, %20, %21, %22, %23, %24, %25, %26, %27, %28, %29, %30, %31}, "
    "{%32, %33, %34, %35}, db, 1, 1, 1, %39;\n}\n"
    : "+f"(d[0]), "+f"(d[1]), "+f"(d[2]), "+f"(d[3]), "+f"(d[4]), "+f"(d[5]), "+f"(d[6]), "+f"(d[7]),
      "+f"(d[8]), "+f"(d[9]), "+f"(d[10]), "+f"(d[11]), "+f"(d[12]), "+f"(d[13]), "+f"(d[14]), "+f"(d[15]),
      "+f"(d[16]), "+f"(d[17]), "+f"(d[18]), "+f"(d[19]), "+f"(d[20]), "+f"(d[21]), "+f"(d[22]), "+f"(d[23]),
      "+f"(d[24]), "+f"(d[25]), "+f"(d[26]), "+f"(d[27]), "+f"(d[28]), "+f"(d[29]), "+f"(d[30]), "+f"(d[31])
    : "r"(a[0]), "r"(a[1]), "r"(a[2]), "r"(a[3]), "r"(blo), "n"(BOFF >> 4), "n"(BHI), "n"(TB));
  } else if constexpr (SCALE == 0) {
  asm volatile("{\n.reg .b32 tb;\n.reg .b64 db;\n"
    "add.u32 tb, %36, %37;\nmov.b64 db, {tb, %38};\n"
    "wgmma.mma_async.sync.aligned.m64n64k16.f32.bf16.bf16 "
    "{%0, %1, %2, %3, %4, %5, %6, %7, %8, %9, %10, %11, %12, %13, %14, %15, "
    "%16, %17, %18, %19, %20, %21, %22, %23, %24, %25, %26, %27, %28, %29, %30, %31}, "
    "{%32, %33, %34, %35}, db, 0, 1, 1, %39;\n}\n"
    : "+f"(d[0]), "+f"(d[1]), "+f"(d[2]), "+f"(d[3]), "+f"(d[4]), "+f"(d[5]), "+f"(d[6]), "+f"(d[7]),
      "+f"(d[8]), "+f"(d[9]), "+f"(d[10]), "+f"(d[11]), "+f"(d[12]), "+f"(d[13]), "+f"(d[14]), "+f"(d[15]),
      "+f"(d[16]), "+f"(d[17]), "+f"(d[18]), "+f"(d[19]), "+f"(d[20]), "+f"(d[21]), "+f"(d[22]), "+f"(d[23]),
      "+f"(d[24]), "+f"(d[25]), "+f"(d[26]), "+f"(d[27]), "+f"(d[28]), "+f"(d[29]), "+f"(d[30]), "+f"(d[31])
    : "r"(a[0]), "r"(a[1]), "r"(a[2]), "r"(a[3]), "r"(blo), "n"(BOFF >> 4), "n"(BHI), "n"(TB));
  } else {
  asm volatile("{\n.reg .b32 tb;\n.reg .b64 db;\n"
    "add.u32 tb, %36, %37;\nmov.b64 db, {tb, %38};\n"
    "wgmma.mma_async.sync.aligned.m64n64k16.f32.bf16.bf16 "
    "{%0, %1, %2, %3, %4, %5, %6, %7, %8, %9, %10, %11, %12, %13, %14, %15, "
    "%16, %17, %18, %19, %20, %21, %22, %23, %24, %25, %26, %27, %28, %29, %30, %31}, "
    "{%32, %33, %34, %35}, db, 0, 1, 1, %39;\n}\n"
    : "=f"(d[0]), "=f"(d[1]), "=f"(d[2]), "=f"(d[3]), "=f"(d[4]), "=f"(d[5]), "=f"(d[6]), "=f"(d[7]),
      "=f"(d[8]), "=f"(d[9]), "=f"(d[10]), "=f"(d[11]), "=f"(d[12]), "=f"(d[13]), "=f"(d[14]), "=f"(d[15]),
      "=f"(d[16]), "=f"(d[17]), "=f"(d[18]), "=f"(d[19]), "=f"(d[20]), "=f"(d[21]), "=f"(d[22]), "=f"(d[23]),
      "=f"(d[24]), "=f"(d[25]), "=f"(d[26]), "=f"(d[27]), "=f"(d[28]), "=f"(d[29]), "=f"(d[30]), "=f"(d[31])
    : "r"(a[0]), "r"(a[1]), "r"(a[2]), "r"(a[3]), "r"(blo), "n"(BOFF >> 4), "n"(BHI), "n"(TB));
  }
}
template <int BOFF, int SCALE, unsigned BHI = 0x40000040u, int TB = 1>
__device__ __forceinline__ void wgmma_rs_n24(float* d, const uint32_t (&a)[4], uint32_t blo) {
  if constexpr (SCALE == 1) {
  asm volatile("{\n.reg .b32 tb;\n.reg .b64 db;\n"
    "add.u32 tb, %16, %17;\nmov.b64 db, {tb, %18};\n"
    "wgmma.mma_async.sync.aligned.m64n24k16.f32.bf16.bf16 "
    "{%0, %1, %2, %3, %4, %5, %6, %7, %8, %9, %10, %11}, "
    "{%12, %13, %14, %15}, db, 1, 1, 1, %19;\n}\n"
    : "+f"(d[0]), "+f"(d[1]), "+f"(d[2]), "+f"(d[3]), "+f"(d[4]), "+f"(d[5]), "+f"(d[6]), "+f"(d[7]),
      "+f"(d[8]), "+f"(d[9]), "+f"(d[10]), "+f"(d[11])
    : "r"(a[0]), "r"(a[1]), "r"(a[2]), "r"(a[3]), "r"(blo), "n"(BOFF >> 4), "n"(BHI), "n"(TB));
  } else if constexpr (SCALE == 0) {
  asm volatile("{\n.reg .b32 tb;\n.reg .b64 db;\n"
    "add.u32 tb, %16, %17;\nmov.b64 db, {tb, %18};\n"
    "wgmma.mma_async.sync.aligned.m64n24k16.f32.bf16.bf16 "
    "{%0, %1, %2, %3, %4, %5, %6, %7, %8, %9, %10, %11}, "
    "{%12, %13, %14, %15}, db, 0, 1, 1, %19;\n}\n"
    : "+f"(d[0]), "+f"(d[1]), "+f"(d[2]), "+f"(d[3]), "+f"(d[4]), "+f"(d[5]), "+f"(d[6]), "+f"(d[7]),
      "+f"(d[8]), "+f"(d[9]), "+f"(d[10]), "+f"(d[11])
    : "r"(a[0]), "r"(a[1]), "r"(a[2]), "r"(a[3]), "r"(blo), "n"(BOFF >> 4), "n"(BHI), "n"(TB));
  } else {
  asm volatile("{\n.reg .b32 tb;\n.reg .b64 db;\n"
    "add.u32 tb, %16, %17;\nmov.b64 db, {tb, %18};\n"
    "wgmma.mma_async.sync.aligned.m64n24k16.f32.bf16.bf16 "
    "{%0, %1, %2, %3, %4, %5, %6, %7, %8, %9, %10, %11}, "
    "{%12, %13, %14, %15}, db, 0, 1, 1, %19;\n}\n"
    : "=f"(d[0]), "=f"(d[1]), "=f"(d[2]), "=f"(d[3]), "=f"(d[4]), "=f"(d[5]), "=f"(d[6]), "=f"(d[7]),
      "=f"(d[8]), "=f"(d[9]), "=f"(d[10]), "=f"(d[11])
    : "r"(a[0]), "r"(a[1]), "r"(a[2]), "r"(a[3]), "r"(blo), "n"(BOFF >> 4), "n"(BHI), "n"(TB));
  }
}

__device__ __forceinline__ void colsum_gather(int b0, int b1, int j, int lane, unsigned tag, uint32_t cs_smem) {
  const unsigned long long* p0 = &g_cs[j][b0][lane * 2];
  const unsigned long long* p1 = &g_cs[j][b1][lane * 2];
#pragma unroll 1
  for (int it = 0; it < 20000; it++) {
    uint4 a = ldcg128(p0), b = ldcg128(p1);
    const bool ok = a.y == tag && a.w == tag && b.y == tag && b.w == tag;
    asm volatile("st.shared.v2.u32 [%0], {%1,%2};" ::"r"(cs_smem + (b0 * 64 + lane * 2) * 4), "r"(a.x), "r"(a.z) : "memory");
    asm volatile("st.shared.v2.u32 [%0], {%1,%2};" ::"r"(cs_smem + (b1 * 64 + lane * 2) * 4), "r"(b.x), "r"(b.z) : "memory");
    if (__all_sync(0xffffffffu, ok)) break;
    __nanosleep(200);
  }
}

__device__ __forceinline__ void spare_cta(int s, const Maps& maps, uint32_t sb, int warp) {
  const int tid = threadIdx.x, lane = tid & 31;
  const int wg = warp < 8 ? warp >> 2 : warp & 1;
  const uint32_t ring = sb + wg * 98304, full = sb + 196608 + wg * 256, empty = full + 128, ones = sb + 196608 + 512;
  if (warp >= 8) {
    if (elect_one()) {
      if (warp < 10) {
#pragma unroll
        for (int i = 0; i < 12; i++) { mbar_init(full + i * 8, 1); mbar_init(empty + i * 8, 1); }
        asm volatile("fence.mbarrier_init.release.cluster;" ::: "memory");
      } else {
        prefetch_map(&maps.qkv2);
      }
    }
  } else if (tid < 64) { sts32(ones + tid * 4, 0x3F803F80u); fence_async_smem(); }
  __syncthreads();
  const int j = s * 2 + wg;
  if (warp >= 8) {
    if (elect_one()) {
      const int par = (warp >> 1) & 1;
      uint32_t ph = 1;
      int slot = par;
#pragma unroll 1
      for (int grp = 0; grp < 9; grp++) {
        const CUtensorMap* map = grp < 3 ? &maps.qkv2 : ((grp & 1) ? &maps.g : &maps.u);
        const int col = grp < 3 ? (grp == 2 ? 0 : grp + 1) * D_ + j * 64 : j * FS + ((grp - 3) >> 1) * 64;
        if (grp == 1) prefetch_map(par ? &maps.g : &maps.u);
#pragma unroll
        for (int b = 0; b < 4; b++) {
          mbar_wait_par(empty + slot * 8, ph);
          mbar_expect_tx(full + slot * 8, 8192);
          tma2d(ring + slot * 8192, map, col, b * 128 + par * 64, full + slot * 8);
          slot += 2;
          if (slot >= 12) { slot -= 12; ph ^= 1; }
        }
      }
    }
  } else {
    const unsigned ep = ldcg32(&g_epoch[(128 + s) * 8]);
    const uint32_t dA = ((ring & 0x3FFFF) >> 4) | (1u << 16), dB = ((ones & 0x3FFFF) >> 4) | ((128u >> 4) << 16);
    int slot = 0, prev = -1; uint32_t ph = 0;
#pragma unroll 1
    for (int grp = 0; grp < 9; grp++) {
      float d[4] = {0.f, 0.f, 0.f, 0.f};
#pragma unroll 1
      for (int b = 0; b < 8; b++) {
        mbar_wait_par(full + slot * 8, ph);
        wg_fence();
        SFOR(k, 4)
          wgmma_ss_n8<k * 2048, 0, 1, 0x10u, 0x40000040u, 1, 0>(d, dA + slot * 512, dB);
        SEND
        wg_commit();
        wg_wait<1>();
        if ((tid & 127) == 0 && prev >= 0) mbar_arrive(empty + prev * 8);
        prev = slot;
        if (++slot == 12) { slot = 0; ph ^= 1; }
      }
      wg_wait<0>();
      const int blk = grp < 3 ? (grp == 2 ? 0 : grp + 1) : ((grp & 1) ? 3 : 6) + ((grp - 3) >> 1);
      if ((lane & 3) < 2) {
        unsigned long long v = ((unsigned long long)(ep + 1) << 32) | __float_as_uint((lane & 1) ? d[2] : d[0]);
        asm volatile("st.relaxed.gpu.global.b64 [%0], %1;" ::"l"(&g_cs[j][blk][(warp & 3) * 16 + (lane & 1) * 8 + (lane >> 2)]), "l"(v) : "memory");
      }
    }
    float4* z = reinterpret_cast<float4*>(g_kv[(ep & 1) ^ 1][s * 2]);
    for (int i = tid; i < 2 * 1152 / 4; i += 256) z[i] = make_float4(0.f, 0.f, 0.f, 0.f);
    bar_sync<1, 256>();
    if (tid == 0) st_flag(&g_epoch[(128 + s) * 8], ep + 1);
  }
}

__global__ void __cluster_dims__(2, 1, 1) __launch_bounds__(384, 1)
fused_kernel(const __grid_constant__ Maps maps, const __nv_bfloat16* __restrict__ wqkv, const __nv_bfloat16* __restrict__ x_, const __nv_bfloat16* __restrict__ wo_,
             const __nv_bfloat16* __restrict__ wd_, __nv_bfloat16* __restrict__ out) {
  extern __shared__ uint8_t smem_raw[];
  const uint32_t sb = (smem_u32(smem_raw) + 1023) & ~1023u;
  const int tid = threadIdx.x, lane = tid & 31;
  const int warp = __shfl_sync(0xffffffffu, tid >> 5, 0);
  if (blockIdx.x < 4) {
    spare_cta(blockIdx.x, maps, sb, warp);
    return;
  }
  int r, j;
  {
    const int c = blockIdx.x >> 1;
    const int gam = c < 4 ? 15 : (c < 36 ? (c - 4) & 7 : (c < 64 ? 8 + (c - 36) % 7 : 15));
    const int mem = c < 4 ? c - 2 : (c < 36 ? (c - 4) >> 3 : (c < 64 ? (c - 36) / 7 : c - 62));
    r = (gam >> 2) * 4 + mem;
    j = (gam & 3) * 2 + (blockIdx.x & 1);
  }
  const int bid = r * 8 + j;
  auto own = [&](int i) { return (((i + (j >> 1)) & 3) << 1) + (j & 1); };

  PROFG(60);
  if (elect_one()) {
    if (warp == 8) {
#pragma unroll
      for (int s = 0; s < 3; s++) mbar_init(sb + OFF_FULL + s * 8, 1);
      asm volatile("fence.mbarrier_init.release.cluster;" ::: "memory");
      PROFL(54);
#pragma unroll
      for (int s = 0; s < 3; s++) {
        mbar_expect_tx(sb + OFF_FULL + s * 8, 40960);
        tma2d(sb + OFF_X + s * 16384, &maps.x, s * 64, r * 128, sb + OFF_FULL + s * 8);
        tma3d(sb + ring_off(s), &maps.qkv, j * 64, s * 64, 0, sb + OFF_FULL + s * 8);
        if (s == 0) PROFL(55);
      }
      PROFL(56);
    } else if (warp == 11) {
      prefetch_map(&maps.qkv);
    } else if (warp < 8) {
#pragma unroll 1
      for (int i = 3 + warp; i < 2 * NSTEP; i += 8) mbar_init(sb + OFF_FULL + i * 8, i < NSTEP ? 1 : 2);
      asm volatile("fence.mbarrier_init.release.cluster;" ::: "memory");
    } else if (warp == 9) {
      mbar_init(sb + BAR_KVD, 2); mbar_init(sb + BAR_LNQ, 1);
      mbar_init(sb + BAR_KPF, 6); mbar_init(sb + BAR_KPF + 8, 6); mbar_init(sb + BAR_DRN, 2);
#pragma unroll
      for (int i = 0; i < 2; i++) mbar_init(sb + BAR_KVR + i * 8, 2 - i);
#pragma unroll
      for (int i = 0; i < 4; i++) mbar_init(sb + BAR_LN + i * 8, 1);
#pragma unroll
      for (int i = 0; i < 8; i++) mbar_init(sb + BAR_ST2 + i * 8, 4);
    } else if (warp == 10) {
#pragma unroll
      for (int i = 0; i < 8; i++) { mbar_init(sb + BAR_RCV + i * 8, 1); mbar_expect_tx(sb + BAR_RCV + i * 8, 8192); }
      mbar_init(sb + BAR_PEER, 2);
      asm volatile("fence.mbarrier_init.release.cluster;" ::: "memory");
    }
  }
  if (warp >= 10) {
    sts128(sb + OFF_KVB + (tid - 320) * 16, make_uint4(0x3F803F80u, 0x3F803F80u, 0x3F803F80u, 0x3F803F80u));
    fence_async_smem();
  }
  __syncthreads();
  asm volatile("barrier.cluster.arrive.relaxed.aligned;\nbarrier.cluster.wait.aligned;" ::: "memory");

  if (warp >= 8) {
    asm volatile("setmaxnreg.dec.sync.aligned.u32 40;");
    if (warp == 8) {
      if (elect_one()) {
        SFOR(i, 5)
          constexpr int s = i + 3;
          mbar_expect_tx(sb + OFF_FULL + s * 8, 40960);
          tma2d(sb + OFF_X + s * 16384, &maps.x, s * 64, r * 128, sb + OFF_FULL + s * 8);
          mbar_wait(sb + OFF_EMPTY + (s - 3) * 8);
          if (PB == 0) PROFL(20 + s - 3);
          tma3d(sb + ring_off(s), &maps.qkv, j * 64, s * 64, 0, sb + OFF_FULL + s * 8);
          if (s == 4) prefetch_map(&maps.g);
          if (s == 5) prefetch_map(&maps.u);
        SEND
        const int o0 = own(0), o1 = own(1), o2 = own(2), o3 = own(3);
        SFOR(i, NSTEP - 8)
          constexpr int t = i + 8;
          constexpr int dep = ring_dep(t);
          mbar_expect_tx(sb + OFF_FULL + t * 8, 16384);
          if (t != 9 && t != 12 && (t < 37 || t > 40)) mbar_wait(sb + OFF_EMPTY + dep * 8);
          if (t == 37) mbar_wait(sb + BAR_CPY);
          if (dep >= PB && dep < PB + 20) PROFL(20 + dep - PB);
          if constexpr (t < 32) {
            tma2d(sb + ring_off(t), &maps.g, j * FS + ((t - 8) >> 3) * 64, ((t - 8) & 7) * 64, sb + OFF_FULL + t * 8);
            tma2d(sb + ring_off(t) + 8192, &maps.u, j * FS + ((t - 8) >> 3) * 64, ((t - 8) & 7) * 64, sb + OFF_FULL + t * 8);
            if (t == 8) prefetch_map(&maps.out);
            if (t == 22) prefetch_map(&maps.wd);
            if (t == 24) prefetch_map(&maps.wo);
            if (t == 30) prefetch_map(&maps.out64);
          } else {
            constexpr bool half = t == 40 || t == 41 || t >= 46;
            constexpr int s0 = half ? (t & 1) * 2 : (t < 40 ? (t - 32) & 3 : t - 42), s1 = half ? s0 + 1 : s0;
            const int b0 = t < 36 ? o0 ^ 1 : (t < 40 ? o0 : (t < 42 ? o1 : (t < 46 ? o3 ^ 1 : o3)));
            const int b1 = t < 36 ? o1 ^ 1 : (t < 40 ? o2 ^ 1 : (t < 42 ? o1 : (t < 46 ? o2 : o3)));
            tma2d(sb + ring_off(t), s0 == 2 ? &maps.wo : &maps.wd, b0 * 64, s0 == 2 ? j * 64 : j * FS + (s0 == 3 ? 128 : s0 * 64), sb + OFF_FULL + t * 8);
            tma2d(sb + ring_off(t) + 8192, s1 == 2 ? &maps.wo : &maps.wd, b1 * 64, s1 == 2 ? j * 64 : j * FS + (s1 == 3 ? 128 : s1 * 64), sb + OFF_FULL + t * 8);
          }
        SEND
      }
    } else {
      const int hw = warp - 9;
      if (tid == 320) prefetch_l2(wqkv + (size_t)(3 * 64 * 3 * D_) + (size_t)bid * 3840, 3840 * 2);
      const unsigned ep = ldcg32(&g_epoch[bid * 8]);
      const unsigned tag = ep + 1, par = ep & 1;
      if (hw == 0) {
        if (lane == 0) {
          mbar_wait(sb + OFF_FULL + PFW_AT * 8);
          prefetch_l2(wd_ + (size_t)bid * 5504, 5504 * 2); prefetch_l2(wo_ + (size_t)bid * 2048, 2048 * 2);
        }
      } else if (hw == 1) {
        if (lane == 0) {
          mbar_wait(sb + OFF_FULL + INIT_AT * 8);
          asm volatile("cp.async.bulk.tensor.2d.global.shared::cta.bulk_group [%0, {%2, %3}], [%1];" ::"l"(&maps.out),
                       "r"(sb + OFF_X + j * 16384), "r"(j * 64), "r"(r * 128) : "memory");
          asm volatile("cp.async.bulk.commit_group;" ::: "memory");
          asm volatile("cp.async.bulk.wait_group 0;" ::: "memory");
          mbar_arrive(sb + BAR_CPY);
          fence_gpu();
          st_flag(&g_flagR[r][j], tag);
          PROFL(46);
        }
      }
      if (hw < 2) {
        __syncwarp();
        float* kvg = g_kv[par][j] + hw * 512 + lane * 4;
        mbar_wait(sb + BAR_KPF + hw * 8);
        {
#define F4ADD(A, B) __uint_as_float(A.x) + __uint_as_float(B.x), __uint_as_float(A.y) + __uint_as_float(B.y), __uint_as_float(A.z) + __uint_as_float(B.z), __uint_as_float(A.w) + __uint_as_float(B.w)
          const uint32_t o = sb + OFF_KVB + 1024 + hw * 4352 + lane * 16;
          float rr[20];
#pragma unroll
          for (int i = 0; i < 5; i++) {
            uint4 a0 = lds128(o + i * 512), a1 = lds128(o + 2176 + i * 512);
            if (i < 4 || lane < 8)
              asm volatile("atom.relaxed.gpu.global.add.v4.f32 {%0,%1,%2,%3}, [%4], {%5,%6,%7,%8};"
                           : "=f"(rr[i * 4]), "=f"(rr[i * 4 + 1]), "=f"(rr[i * 4 + 2]), "=f"(rr[i * 4 + 3])
                           : "l"(i < 4 ? kvg + i * 128 : kvg + 1024 - hw * 480), "f"(__uint_as_float(a0.x) + __uint_as_float(a1.x)),
                             "f"(__uint_as_float(a0.y) + __uint_as_float(a1.y)), "f"(__uint_as_float(a0.z) + __uint_as_float(a1.z)),
                             "f"(__uint_as_float(a0.w) + __uint_as_float(a1.w)) : "memory");
            else rr[16] = rr[17] = rr[18] = rr[19] = 0.f;
          }
          uint32_t x = 0;
#pragma unroll
          for (int i = 0; i < 20; i++) x ^= __float_as_uint(rr[i]);
          consume(x, sb + OFF_PAR);
        }
        __syncwarp();
        if (lane == 0) {
          mbar_arrive(sb + BAR_KVD);
          mbar_wait(sb + BAR_KVD);
          if (hw == 1) { st_flag(&g_flagK[j][r], tag); PROFL(47); }
        }
        __syncwarp();
        wait_flags(lane < 16 ? &g_flagK[j][lane] : &g_flagR[r][lane - 16], lane < 16 + hw * 8, tag);
        if (hw == 0) PROFL(48);
        const float* kv = g_kv[par][j];
        uint4 d[4];
#pragma unroll
        for (int i = 0; i < 4; i++) d[i] = ldcg128(kv + ((hw * 4 + i) * 32 + lane) * 4);
        uint4 z = ldcg128(kv + 1024 + (hw * 8 + (lane & 7)) * 4);
#pragma unroll
        for (int h = 0; h < 2; h++) {
          const uint32_t o = sb + OFF_KVF + (hw * 2 + h) * 768 + lane * 4;
          sts32(o + 0, pack_bf16(__uint_as_float(d[2 * h].x), __uint_as_float(d[2 * h].y)));
          sts32(o + 128, pack_bf16(__uint_as_float(d[2 * h + 1].x), __uint_as_float(d[2 * h + 1].y)));
          sts32(o + 256, pack_bf16(__uint_as_float(d[2 * h].z), __uint_as_float(d[2 * h].w)));
          sts32(o + 384, pack_bf16(__uint_as_float(d[2 * h + 1].z), __uint_as_float(d[2 * h + 1].w)));
        }
        {
          const uint32_t z0 = pack_bf16(__uint_as_float(z.x), __uint_as_float(z.y)), z1 = pack_bf16(__uint_as_float(z.z), __uint_as_float(z.w));
          const uint32_t o = sb + OFF_KVF + (hw * 2 + ((lane >> 2) & 1)) * 768 + 512 + (lane >> 3) * 32 + (lane & 3) * 4;
          sts32(o, z0); sts32(o + 16, z0); sts32(o + 128, z1); sts32(o + 144, z1);
        }
        fence_async_smem();
        __syncwarp();
        if (lane == 0) {
          mbar_arrive(sb + BAR_KVR);
          if (hw == 0) { PROFL(49); st_flag(&g_epoch[bid * 8], tag); }
        }
      } else {
#pragma unroll 1
        for (int ph = 0; ph < 5; ph++) {
          mbar_wait(sb + OFF_FULL + (ph == 0 ? 5 : (ph == 1 ? 9 : ph * 8 - 3)) * 8);
          colsum_gather(ph == 0 ? 1 : (ph == 1 ? 0 : ph + 1), ph == 0 ? 2 : (ph == 1 ? 0 : ph + 4), j, lane, tag, sb + OFF_CS);
          __syncwarp();
          if (lane == 0) mbar_arrive(sb + (ph == 0 ? BAR_LN : (ph == 1 ? BAR_LNQ : BAR_LN + (ph - 1) * 8)));
          PROFL(41 + ph);
        }
      }
      if (hw < 2 && elect_one()) {
        mbar_wait(sb + BAR_KVR);
        asm volatile("fence.proxy.async;" ::: "memory");
#pragma unroll 1
        for (int p = 0; p < 4; p++) {
          const int col = own(p) * 64;
          mbar_wait(sb + BAR_ST2 + p * 16 + hw * 8);
          fence_async_smem();
          asm volatile("cp.reduce.async.bulk.tensor.2d.global.shared::cta.add.bulk_group [%0, {%2, %3}], [%1];" ::"l"(&maps.out64),
                       "r"(sb + OFF_X + p * 16384 + hw * 8192), "r"(col), "r"(r * 128 + hw * 64) : "memory");
          asm volatile("cp.async.bulk.commit_group;" ::: "memory");
          if (hw == 0) PROFL(51 + p);
        }
        asm volatile("cp.async.bulk.wait_group.read 0;" ::: "memory");
        PROFL(57 + hw);
      }
      __syncwarp();
    }
  } else {
    asm volatile("setmaxnreg.inc.sync.aligned.u32 232;");
    const int wg = warp >> 2, wq = warp & 3;
    const bool elected = (tid & 127) == 0;
    const uint32_t dA0 = (((sb + OFF_X + wg * 8192) & 0x3FFFF) >> 4) | (1u << 16);
    const uint32_t dB0 = ((sb & 0x3FFFF) >> 4) | ((8192u >> 4) << 16);
    const uint32_t frow = (lane & 7) + ((lane >> 3) & 1) * 8, fhi = lane >> 4;
    const uint32_t stg = sb + OFF_X + (warp * 16 + frow) * 128;
    uint32_t Hf[15][4];
    float acc1[96], accA[64];
    float* const accB = acc1;
    float qt[24];
    float* const accC = accA;
    float nm0, nm1, rs0, rs1;
#define RELEASE(T) do { if (elected) mbar_arrive(sb + ((T) == 9 ? BAR_DRN : OFF_EMPTY + (T) * 8)); } while (0)

    uint32_t af[2][4][4];
    uint32_t cc0, cc1;
    float sm0 = 0.f, sm1 = 0.f, sq0 = 0.f, sq1 = 0.f;
    auto stats = [&](const uint32_t (&f)[4][4], int row) __attribute__((always_inline)) {
      const uint32_t cc = row ? cc1 : cc0;
      uint32_t d = bsub2(f[0][row], cc), e = bsub2(f[0][row + 2], cc);
      uint32_t qd = bmul2(d, d), qe = bmul2(e, e);
#pragma unroll
      for (int k = 1; k < 4; k++) {
        uint32_t d2 = bsub2(f[k][row], cc), e2 = bsub2(f[k][row + 2], cc);
        d = badd2(d, d2); e = badd2(e, e2);
        qd = bfma2(d2, d2, qd); qe = bfma2(e2, e2, qe);
      }
      d = badd2(d, e); qd = badd2(qd, qe);
      if (row) { sm1 += bflo(d) + bfhi(d); sq1 += bflo(qd) + bfhi(qd); }
      else { sm0 += bflo(d) + bfhi(d); sq0 += bflo(qd) + bfhi(qd); }
    };
    {
      uint32_t la[4];
#pragma unroll
      for (int k = 0; k < 4; k++) la[k] = stg + (((k * 2 + fhi) ^ (lane & 7)) << 4);
#pragma unroll
      for (int i = 0; i < 96; i++) asm volatile("mov.f32 %0, 0f00000000;" : "=f"(acc1[i]));
      mbar_wait(sb + OFF_FULL);
      PROF(1);
#pragma unroll
      for (int k = 0; k < 4; k++) ldsm4(af[0][k], la[k]);
      uint32_t bdesc = dB0 + (OFF_RING >> 4), slot = 0;
#pragma unroll 1
      for (int s2 = 0; s2 < 8; s2 += 2) {
        SFOR(h, 2)
          const int s = s2 + h;
          wg_fence();
          wgmma_rs_n192<0, 1>(acc1, af[h][0], bdesc);
          wgmma_rs_n192<2048, 1>(acc1, af[h][1], bdesc);
          wg_commit();
          wg_wait<1>();
          if (h == 1 || s2 > 0) {
            if (elected) mbar_arrive(sb + OFF_EMPTY + (s - 1) * 8);
          } else {
            float p0 = (bflo(af[0][0][0]) + bfhi(af[0][0][0])) + (bflo(af[0][0][2]) + bfhi(af[0][0][2]));
            float p1 = (bflo(af[0][0][1]) + bfhi(af[0][0][1])) + (bflo(af[0][0][3]) + bfhi(af[0][0][3]));
            p0 += __shfl_xor_sync(0xffffffffu, p0, 1); p1 += __shfl_xor_sync(0xffffffffu, p1, 1);
            p0 += __shfl_xor_sync(0xffffffffu, p0, 2); p1 += __shfl_xor_sync(0xffffffffu, p1, 2);
            cc0 = pack_bf16(p0 * 0.0625f, p0 * 0.0625f); cc1 = pack_bf16(p1 * 0.0625f, p1 * 0.0625f);
          }
          stats(af[h], 0);
          wg_fence();
          wgmma_rs_n192<4096, 1>(acc1, af[h][2], bdesc);
          mbar_wait(sb + OFF_FULL + (s + 1) * 8);
          if (h == 0 || s2 < 6) {
#pragma unroll
            for (int k = 0; k < 4; k++) ldsm4(af[h ^ 1][k], la[k] + (s + 1) * 16384);
          }
          wgmma_rs_n192<6144, 1>(acc1, af[h][3], bdesc);
          wg_commit();
          stats(af[h], 1);
          slot = slot == 2 ? 0 : slot + 1;
          bdesc = dB0 + ((OFF_RING + slot * 24576) >> 4);
        SEND
      }
    }
    PROF(2);

    const uint32_t csb = sb + OFF_CS + (lane & 3) * 8;
#define G1_STEP(WG, ACC, T, S, FIRST, PRE, SLOT_A, SLOT_B, EXTRA, SLOT_C)                       \
  {                                                                                            \
    PRE                                                                                        \
    wg_fence();                                                                                \
    WG<(S) * 16384 + 0, ring_off(T) + 0, (S) == 0 ? (FIRST) : 1>(ACC, dA0, dB0);               \
    WG<(S) * 16384 + 32, ring_off(T) + 2048, 1>(ACC, dA0, dB0);                                \
    wg_commit();                                                                               \
    wg_wait<1>();                                                                              \
    RELEASE((T) - 1);                                                                          \
    SLOT_A                                                                                     \
    if (MERGEB) { SLOT_B }                                                                     \
    const uint32_t rdy = mbar_test(sb + OFF_FULL + ((T) + 1) * 8);                             \
    wg_fence();                                                                                \
    WG<(S) * 16384 + 64, ring_off(T) + 4096, 1>(ACC, dA0, dB0);                                \
    if (!MERGEB) { SLOT_B }                                                                    \
    WG<(S) * 16384 + 96, ring_off(T) + 6144, 1>(ACC, dA0, dB0);                                \
    EXTRA                                                                                      \
    wg_commit();                                                                               \
    SLOT_C                                                                                     \
    if (!rdy) mbar_wait(sb + OFF_FULL + ((T) + 1) * 8);                                        \
  }
#define G1_STEPK(WG, ACC, T, S, PRE, SLOT_A, SLOT_B, SLOT_C)                                    \
  {                                                                                            \
    PRE                                                                                        \
    wg_fence();                                                                                \
    WG<(S) * 16384 + 0, ring_off(T) + 0, 1>(ACC, dA0, dB0);                                    \
    KV_MMA(0);                                                                                 \
    WG<(S) * 16384 + 32, ring_off(T) + 2048, 1>(ACC, dA0, dB0);                                \
    KV_MMA(1);                                                                                 \
    wg_commit();                                                                               \
    wg_wait<1>();                                                                              \
    RELEASE((T) - 1);                                                                          \
    SLOT_A                                                                                     \
    if (MERGEB) { SLOT_B }                                                                     \
    const uint32_t rdy = mbar_test(sb + OFF_FULL + ((T) + 1) * 8);                             \
    wg_fence();                                                                                \
    WG<(S) * 16384 + 64, ring_off(T) + 4096, 1>(ACC, dA0, dB0);                                \
    KV_MMA(2);                                                                                 \
    if (!MERGEB) { SLOT_B }                                                                    \
    WG<(S) * 16384 + 96, ring_off(T) + 6144, 1>(ACC, dA0, dB0);                                \
    KV_MMA(3);                                                                                 \
    wg_commit();                                                                               \
    SLOT_C                                                                                     \
    if (!rdy) mbar_wait(sb + OFF_FULL + ((T) + 1) * 8);                                        \
  }
#define PHI_FIN(k0, k1, k2, k3, D0, D1)                                                                         \
  {                                                                                                             \
    float p0 = k0 > 0.f ? fmaf(k0, rs0, 1.000001f) : ex2f(k0 * l0) + 1e-6f;                                     \
    float p1 = k1 > 0.f ? fmaf(k1, rs0, 1.000001f) : ex2f(k1 * l0) + 1e-6f;                                     \
    float p2 = k2 > 0.f ? fmaf(k2, rs1, 1.000001f) : ex2f(k2 * l1) + 1e-6f;                                     \
    float p3 = k3 > 0.f ? fmaf(k3, rs1, 1.000001f) : ex2f(k3 * l1) + 1e-6f;                                     \
    D0 = pack_bf16(p0, p1);                                                                                     \
    D1 = pack_bf16(p2, p3);                                                                                     \
  }
    float2 ca, cb, cc, cd;
#define LDC(V, COL) V = lds64f(csb + (COL) * 4);
#define PHI_BLOCK(CS, CQ, D0, D1)                                                                               \
  {                                                                                                             \
    const float* a = &acc1[((CQ) >> 3) * 4];                                                                    \
    float k0 = fmaf(nm0, CS.x, a[0]), k1 = fmaf(nm0, CS.y, a[1]), k2 = fmaf(nm1, CS.x, a[2]), k3 = fmaf(nm1, CS.y, a[3]); \
    PHI_FIN(k0, k1, k2, k3, D0, D1)                                                                             \
  }
#define Q_SAVE(CS, NB)                                                                                          \
  {                                                                                                             \
    qt[(NB) * 4 + 0] = fmaf(nm0, CS.x, acc1[(NB) * 4 + 0]); qt[(NB) * 4 + 1] = fmaf(nm0, CS.y, acc1[(NB) * 4 + 1]); \
    qt[(NB) * 4 + 2] = fmaf(nm1, CS.x, acc1[(NB) * 4 + 2]); qt[(NB) * 4 + 3] = fmaf(nm1, CS.y, acc1[(NB) * 4 + 3]); \
    asm volatile("" : "+f"(qt[(NB) * 4 + 0]), "+f"(qt[(NB) * 4 + 1]), "+f"(qt[(NB) * 4 + 2]), "+f"(qt[(NB) * 4 + 3])); \
  }
#define V_BLOCK(CS, CV, D0, D1)                                                                                 \
  {                                                                                                             \
    const float* a = &acc1[((CV) >> 3) * 4];                                                                    \
    D0 = pack_bf16(fmaf(nm0, CS.x, a[0]) * rs0, fmaf(nm0, CS.y, a[1]) * rs0);                                   \
    D1 = pack_bf16(fmaf(nm1, CS.x, a[2]) * rs1, fmaf(nm1, CS.y, a[3]) * rs1);                                   \
  }
    float kvd[16];
    {
      const uint32_t dV = (((sb + OFF_KVT + wg * 8192) & 0x3FFFF) >> 4) | (((OFF_KVB - OFF_KVT - wg * 8192) >> 4) << 16);
      const uint32_t dK = (((sb + OFF_KVT + 4096 + wg * 8192) & 0x3FFFF) >> 4) | (1u << 16);
      const uint32_t kta = sb + OFF_KVT + wg * 8192 + (wq * 16 + frow) * 64;
      const uint32_t ksw0 = (fhi ^ ((frow >> 1) & 3)) << 4, ksw1 = ((2 + fhi) ^ ((frow >> 1) & 3)) << 4;
      float l0, l1;
#define WG_BAR() do { if (wg == 0) bar_sync<1, 128>(); else bar_sync<2, 128>(); } while (0)
#define KV_MMA(k) wgmma_ss_n32<((k) * 64 - ((k) * 64 << 16)) * 16, (k) * 1024, (k) != 0 ? 1 : -1, 0x80000020u, 0x80000020u, 1, 1>(kvd, dV, dK)
#define O_MMA(H, OD) wgmma_rs_n24<(H) * 768, -1, 0x10u, 0>(OD, Hf[H], dO)
#define O_FIN(H, OD)                                                                                        \
  {                                                                                                         \
    const float i0 = rcpf_(OD[8] + 1e-6f); const float i1 = rcpf_(OD[10] + 1e-6f);                          \
    Hf[H][0] = pack_bf16(OD[0] * i0, OD[1] * i0); Hf[H][1] = pack_bf16(OD[2] * i1, OD[3] * i1);             \
    Hf[H][2] = pack_bf16(OD[4] * i0, OD[5] * i0); Hf[H][3] = pack_bf16(OD[6] * i1, OD[7] * i1);             \
  }
#define U4F(a, b, c, d) make_uint4(__float_as_uint(a), __float_as_uint(b), __float_as_uint(c), __float_as_uint(d))
#define KV_RED(U)                                                                               \
  if (wq < 3) {                                                                                 \
    if (wq == 0) {                                                                              \
      sts128(kvp + (U) * 4352, U4F(kvd[0], kvd[1], kvd[2], kvd[3]));                            \
      sts128(kvp + (U) * 4352 + 512, U4F(kvd[4], kvd[5], kvd[6], kvd[7]));                      \
    } else if (wq == 1) {                                                                       \
      sts128(kvp + (U) * 4352 + 1024, U4F(kvd[8], kvd[9], kvd[10], kvd[11]));                   \
      sts128(kvp + (U) * 4352 + 1536, U4F(kvd[12], kvd[13], kvd[14], kvd[15]));                 \
    } else if (lane < 4) {                                                                      \
      sts128(kvp + (U) * 4352 + 2048, U4F(kvd[0], kvd[1], kvd[4], kvd[5]));                     \
      sts128(kvp + (U) * 4352 + 2048 + 64, U4F(kvd[8], kvd[9], kvd[12], kvd[13]));              \
    }                                                                                           \
    __syncwarp();                                                                               \
    if (lane == 0) mbar_arrive(sb + BAR_KPF + (U) * 8);                                         \
  }
      const uint32_t kvp = sb + OFF_KVB + 1024 + wg * 2176 + lane * 16;
      uint32_t pp[4];
#define K_HALF(CS, H, B) PHI_BLOCK(CS, 64 + (H) * 16 + (B) * 8, pp[(B) * 2], pp[(B) * 2 + 1])
#define LDK(V, H, B) LDC(V, 64 + (H) * 16 + (B) * 8)
#define LDV(H) LDC(cb, 128 + (H) * 16) LDC(cc, 128 + (H) * 16 + 8)
#define K_ST(H) stsm4(kta + 4096 + (((H) & 1) ? ksw1 : ksw0), pp[0], pp[1], pp[2], pp[3]);
      uint32_t pv[4];
#define V_CALC(H) { V_BLOCK(cb, 128 + (H) * 16, pv[0], pv[1]) V_BLOCK(cc, 128 + (H) * 16 + 8, pv[2], pv[3]) }
#define V_ST(H) stsm4(kta + (((H) & 1) ? ksw1 : ksw0), pv[0], pv[1], pv[2], pv[3]);
      G1_STEP(wgmma_ss_n128, accA, 8, 0, -1, ,
        {
          _Pragma("unroll") for (int o = 1; o < 4; o <<= 1) {
            sm0 += __shfl_xor_sync(0xffffffffu, sm0, o); sq0 += __shfl_xor_sync(0xffffffffu, sq0, o);
            sm1 += __shfl_xor_sync(0xffffffffu, sm1, o); sq1 += __shfl_xor_sync(0xffffffffu, sq1, o);
          }
        },
        {
          sm0 *= (1.f / D_); sm1 *= (1.f / D_);
          nm0 = -(bflo(cc0) + sm0); nm1 = -(bflo(cc1) + sm1);
          rs0 = rsqrtf(fmaxf(fmaf(-sm0, sm0, sq0 * (1.f / D_)), 0.f) + 1e-5f);
          rs1 = rsqrtf(fmaxf(fmaf(-sm1, sm1, sq1 * (1.f / D_)), 0.f) + 1e-5f);
          l0 = rs0 * 1.4426950408889634f; l1 = rs1 * 1.4426950408889634f;
          mbar_wait(sb + BAR_LN); LDK(ca, 0, 0)
        }, ,
        { K_HALF(ca, 0, 0) })
      PROF(3);
      G1_STEP(wgmma_ss_n128, accA, 9, 1, 1, { LDK(ca, 0, 1) LDV(0) }, { K_HALF(ca, 0, 1) }, { V_CALC(0) }, , )
      uint32_t pw[4];
      G1_STEP(wgmma_ss_n128, accA, 10, 2, 1, { LDV(1) LDK(ca, 1, 0) },
              { V_BLOCK(cb, 144, pw[0], pw[1]) V_BLOCK(cc, 152, pw[2], pw[3]) }, , ,
              { mbar_wait(sb + BAR_DRN); K_ST(0) V_ST(0) stsm4(kta + ksw1, pw[0], pw[1], pw[2], pw[3]); K_HALF(ca, 1, 0) })
      G1_STEP(wgmma_ss_n128, accA, 11, 3, 1, { LDK(ca, 1, 1) LDK(cb, 2, 0) }, { K_HALF(ca, 1, 1) K_ST(1) }, { K_HALF(cb, 2, 0) fence_async_smem(); }, , { WG_BAR(); })
      G1_STEPK(wgmma_ss_n128, accA, 12, 4, { LDK(ca, 2, 1) LDV(2) }, { K_HALF(ca, 2, 1) }, { V_CALC(2) }, )
      G1_STEP(wgmma_ss_n128, accA, 13, 5, 1, { LDV(3) LDK(ca, 3, 0) }, { K_ST(2) V_ST(2) V_CALC(3) V_ST(3) }, { K_HALF(ca, 3, 0) }, , { KV_RED(0) })
      G1_STEP(wgmma_ss_n128, accA, 14, 6, 1, { mbar_wait(sb + BAR_LNQ); LDK(ca, 3, 1) LDC(cb, 48) }, { K_HALF(ca, 3, 1) K_ST(3) }, { PHI_BLOCK(cb, 48, Hf[3][0], Hf[3][1]) fence_async_smem(); }, , { WG_BAR(); })
      G1_STEPK(wgmma_ss_n128, accA, 15, 7, { LDC(ca, 56) LDC(cb, 0) LDC(cc, 8) LDC(cd, 16) },
               { PHI_BLOCK(ca, 56, Hf[3][2], Hf[3][3]) LDC(ca, 24) },
               { Q_SAVE(cb, 0) Q_SAVE(cc, 1) Q_SAVE(cd, 2) LDC(cb, 32) LDC(cc, 40) },
               { Q_SAVE(ca, 3) Q_SAVE(cb, 4) Q_SAVE(cc, 5) mbar_wait(sb + BAR_LN + 8); })
      PROF(4);

      const float ga0 = 0.7978845608028654f * rs0, ga1 = 0.7978845608028654f * rs1;
      const float gb0 = 0.7978845608028654f * 0.044715f * rs0 * rs0 * rs0, gb1 = 0.7978845608028654f * 0.044715f * rs1 * rs1 * rs1;
      const float gc0 = 0.5f * rs0 * rs0, gc1 = 0.5f * rs1 * rs1;

#define GEGLU_BLOCK(ACC, NB, UOFF, cg, cu, DST0, DST1)                                           \
  {                                                                                              \
    float g0 = fmaf(nm0, cg.x, ACC[(NB) * 4 + 0]), g1 = fmaf(nm0, cg.y, ACC[(NB) * 4 + 1]);       \
    float g2 = fmaf(nm1, cg.x, ACC[(NB) * 4 + 2]), g3 = fmaf(nm1, cg.y, ACC[(NB) * 4 + 3]);       \
    float u0 = fmaf(nm0, cu.x, ACC[(UOFF) + (NB) * 4 + 0]), u1 = fmaf(nm0, cu.y, ACC[(UOFF) + (NB) * 4 + 1]); \
    float u2 = fmaf(nm1, cu.x, ACC[(UOFF) + (NB) * 4 + 2]), u3 = fmaf(nm1, cu.y, ACC[(UOFF) + (NB) * 4 + 3]); \
    float t0 = tanhf_(g0 * fmaf(g0 * g0, gb0, ga0)), t1 = tanhf_(g1 * fmaf(g1 * g1, gb0, ga0));   \
    float t2 = tanhf_(g2 * fmaf(g2 * g2, gb1, ga1)), t3 = tanhf_(g3 * fmaf(g3 * g3, gb1, ga1));   \
    float m0 = g0 * u0 * gc0, m1 = g1 * u1 * gc0, m2 = g2 * u2 * gc1, m3 = g3 * u3 * gc1;         \
    DST0 = pack_bf16(fmaf(m0, t0, m0), fmaf(m1, t1, m1));                                        \
    DST1 = pack_bf16(fmaf(m2, t2, m2), fmaf(m3, t3, m3));                                        \
  }

      SFOR(s, 8)
        constexpr int t = 16 + s;
        G1_STEP(wgmma_ss_n128, accB, t, s, 0, { LDC(ca, 192 + s * 8) LDC(cb, 384 + s * 8) },
          { if constexpr (s == 0) { if (elected) mbar_arrive(sb + OFF_EMPTY + 9 * 8); KV_RED(1) }
            GEGLU_BLOCK(accA, s, 32, ca, cb, Hf[4 + (s >> 1)][(s & 1) * 2], Hf[4 + (s >> 1)][(s & 1) * 2 + 1]) },
          { if constexpr (s >= 1 && s < 7) { constexpr int b = s - 1; PHI_FIN(qt[b * 4], qt[b * 4 + 1], qt[b * 4 + 2], qt[b * 4 + 3], Hf[b >> 1][(b & 1) * 2], Hf[b >> 1][(b & 1) * 2 + 1]) } }, , )
      SEND
      PROF(6);
      float od[12], oe[12];
      const uint32_t dO = (((sb + OFF_KVF) & 0x3FFFF) >> 4) | ((128u >> 4) << 16);
      SFOR(s, 8)
        constexpr int t = 24 + s;
        G1_STEP(wgmma_ss_n112, accC, t, s, 0,
          { if constexpr (s == 0) mbar_wait(sb + BAR_LN + 16);
            LDC(ca, 256 + s * 8) LDC(cb, 448 + s * 8) },
          { GEGLU_BLOCK(accB, s, 32, ca, cb, Hf[8 + (s >> 1)][(s & 1) * 2], Hf[8 + (s >> 1)][(s & 1) * 2 + 1]) },
          { if constexpr (s == 7) { O_FIN(0, od) O_FIN(1, oe) } },
          { if constexpr (s >= 6) {
              if constexpr (s == 6) mbar_wait(sb + BAR_KVR);
              if constexpr (s == 7) wg_fence();
              O_MMA((s - 6) * 2, od); O_MMA((s - 6) * 2 + 1, oe);
            } }, )
      SEND
      PROF(8);

      uint32_t rx, rbar;
      asm volatile("mapa.shared::cluster.u32 %0, %1, %2;" : "=r"(rx) : "r"(sb + OFF_X + warp * 2048 + lane * 16), "r"((j & 1) ^ 1));
      asm volatile("mapa.shared::cluster.u32 %0, %1, %2;" : "=r"(rbar) : "r"(sb + BAR_RCV + wg * 8), "r"((j & 1) ^ 1));
      const uint32_t lx = sb + OFF_X + warp * 2048 + lane * 16;
#define G2_SEND(ACC, K, I0, I1)                                                                          \
  {                                                                                                      \
    _Pragma("unroll") for (int i = (I0); i < (I1); i++) {                                                \
      uint32_t a0 = pack_bf16((ACC)[i * 8 + 0], (ACC)[i * 8 + 1]), a1 = pack_bf16((ACC)[i * 8 + 2], (ACC)[i * 8 + 3]); \
      uint32_t a2 = pack_bf16((ACC)[i * 8 + 4], (ACC)[i * 8 + 5]), a3 = pack_bf16((ACC)[i * 8 + 6], (ACC)[i * 8 + 7]); \
      st_async4(rx + (K) * 16384 + i * 512, a0, a1, a2, a3, rbar + (K) * 16);                            \
    }                                                                                                    \
  }
      uint4 rv[4];
#define G2_RLD(K, I0, I1)                                                                                \
  {                                                                                                      \
    if ((I0) == 0) mbar_wait(sb + BAR_RCV + (K) * 16 + wg * 8);                                          \
    _Pragma("unroll") for (int i = (I0); i < (I1); i++) rv[i] = lds128(lx + (K) * 16384 + i * 512); \
  }
#define G2_OWN(ACC, K, I0, I1)                                                                           \
  {                                                                                                      \
    _Pragma("unroll") for (int i = (I0); i < (I1); i++) {                                                \
      uint32_t a0 = pack_bf16((ACC)[i * 8 + 0], (ACC)[i * 8 + 1]), a1 = pack_bf16((ACC)[i * 8 + 2], (ACC)[i * 8 + 3]); \
      uint32_t a2 = pack_bf16((ACC)[i * 8 + 4], (ACC)[i * 8 + 5]), a3 = pack_bf16((ACC)[i * 8 + 6], (ACC)[i * 8 + 7]); \
      stsm4(stg + (K) * 16384 + (((i * 2 + fhi) ^ (lane & 7)) << 4), badd2(a0, rv[i].x), badd2(a1, rv[i].y),     \
            badd2(a2, rv[i].z), badd2(a3, rv[i].w));                                                     \
    }                                                                                                    \
    if ((I1) == 4) {                                                                                     \
      __syncwarp();                                                                                      \
      if (lane == 0) mbar_arrive(sb + BAR_ST2 + (K) * 16 + wg * 8);                                      \
    }                                                                                                    \
  }
#define G2_RED(K)                                                                                        \
  {                                                                                                      \
    char* const ob = reinterpret_cast<char*>(out + (size_t)(r * 128 + warp * 16 + (lane >> 3)) * D_ + own(K) * 64 + (lane & 7) * 8); \
    _Pragma("unroll") for (int i = 0; i < 4; i++) {                                                      \
      const int row = i * 4 + (lane >> 3);                                                               \
      uint4 v = lds128(sb + OFF_X + (K) * 16384 + (warp * 16 + row) * 128 + (((lane & 7) ^ (row & 7)) << 4)); \
      red_bf16x8(ob + i * 4096, v);                                                                      \
    }                                                                                                    \
  }
#define G2_PASS(WG, ACC, T0, BOX, WAITF, PRE, SLOT_A, SLOT_C)                                            \
  SFOR(s, 4)                                                                                             \
    constexpr int t = (T0) + s;                                                                          \
    constexpr int hb = s == 0 ? 4 : (s == 1 ? 8 : (s == 2 ? 0 : 12));                                    \
    PRE                                                                                                  \
    wg_fence();                                                                                          \
    WG<ring_off(t) + (BOX), s != 0>(ACC, Hf[hb], dB0);                                                   \
    WG<ring_off(t) + (BOX) + 2048, 1>(ACC, Hf[hb + 1], dB0);                                             \
    if constexpr (s < 3) WG<ring_off(t) + (BOX) + 4096, 1>(ACC, Hf[hb + 2], dB0);                        \
    wg_commit();                                                                                         \
    wg_wait<1>();                                                                                        \
    if constexpr (t - 1 <= 38) RELEASE(t - 1);                                                          \
    SLOT_A                                                                                               \
    const uint32_t rdy = mbar_test(sb + OFF_FULL + (t + 1) * 8);                                         \
    wg_fence();                                                                                          \
    WG<ring_off(t) + (BOX) + (s < 3 ? 6144 : 4096), 1>(ACC, Hf[hb + (s < 3 ? 3 : 2)], dB0);              \
    wg_commit();                                                                                         \
    SLOT_C                                                                                               \
    if (!rdy) mbar_wait(sb + OFF_FULL + (t + 1) * 8);                                                    \
  SEND

      G2_PASS(wgmma_rs_n128, accB, 32, 0, true,
        { if constexpr (s == 0) mbar_wait(sb + BAR_LN + 24);
          if constexpr (s < 3) { LDC(ca, 320 + s * 16) LDC(cb, 512 + s * 16) LDC(cc, 328 + s * 16) LDC(cd, 520 + s * 16) } },
        { if constexpr (s == 0) {
            mbar_wait(sb + BAR_CPY);
            if (elected)
              asm volatile("mbarrier.arrive.relaxed.cluster.shared::cluster.b64 _, [%0];" ::"r"(rbar + (BAR_PEER - BAR_RCV) - wg * 8) : "memory");
            O_FIN(2, od)
          }
          if constexpr (s == 1) O_FIN(3, oe)
          if constexpr (s < 3) GEGLU_BLOCK(accC, s * 2, 32, ca, cb, Hf[12 + s][0], Hf[12 + s][1]) },
        { if constexpr (s < 3) GEGLU_BLOCK(accC, s * 2 + 1, 32, cc, cd, Hf[12 + s][2], Hf[12 + s][3])
          if constexpr (s == 3) mbar_wait(sb + BAR_PEER); })
      PROF(9);
#define G2_HALFPASS(ACC, T0, SLOT)                                                                       \
  SFOR(q, 8)                                                                                             \
    constexpr int t = (T0) + (q >> 2), c = q >> 1;                                                       \
    constexpr int hb = (c == 0 ? 4 : (c == 1 ? 8 : (c == 2 ? 0 : 12))) + (q & 1) * 2;                    \
    constexpr int off = ring_off(t) + (c & 1) * 8192 + (q & 1) * 4096;                                   \
    wg_fence();                                                                                          \
    wgmma_rs_n64<off, q != 0>(ACC, Hf[hb], dB0);                                                         \
    if constexpr (q < 7) wgmma_rs_n64<off + 2048, 1>(ACC, Hf[hb + 1], dB0);                              \
    wg_commit();                                                                                         \
    if constexpr (q == 0) wg_wait<1>();                                                                  \
    SLOT                                                                                                 \
    if constexpr ((q & 3) == 3 && t + 1 < NSTEP) mbar_wait(sb + OFF_FULL + (t + 1) * 8);                 \
  SEND
      G2_PASS(wgmma_rs_n128, accA, 36, 0, true, , { G2_SEND(accB + (s >> 1) * 32, s >> 1, (s & 1) * 2, (s & 1) * 2 + 1) },
        { G2_SEND(accB + (s >> 1) * 32, s >> 1, (s & 1) * 2 + 1, (s & 1) * 2 + 2) if constexpr (s == 3) G2_RLD(0, 0, 4) })
      PROF(12);
      G2_HALFPASS(accB, 40, { if constexpr (q < 2) G2_OWN(accA, 0, q * 2, q * 2 + 2) else if constexpr (q < 6) G2_SEND(accA + 32, 2, q - 2, q - 1)
                              if constexpr (q == 6) G2_RLD(1, 0, 4) })
      PROF(13);
      wg_fence();
      wgmma_rs_n128<ring_off(42), 0>(accA, Hf[4], dB0);
      wg_commit();
      wg_wait<1>();
      G2_OWN(accB, 1, 0, 2)
      wg_fence();
      wgmma_rs_n128<ring_off(42) + 2048, 1>(accA, Hf[5], dB0);
      G2_OWN(accB, 1, 2, 4)
      wgmma_rs_n128<ring_off(42) + 4096, 1>(accA, Hf[6], dB0);
      wgmma_rs_n128<ring_off(42) + 6144, 1>(accA, Hf[7], dB0);
      SFOR(s, 3)
        constexpr int t = 43 + s, hb = s == 0 ? 8 : (s == 1 ? 0 : 12);
        mbar_wait(sb + OFF_FULL + t * 8);
        SFOR(k, (s == 2 ? 3 : 4))
          wgmma_rs_n128<ring_off(t) + k * 2048, 1>(accA, Hf[hb + k], dB0);
        SEND
      SEND
      wg_commit();
      G2_RLD(2, 0, 4)
      mbar_wait(sb + OFF_FULL + 46 * 8);
      PROF(14);
      G2_HALFPASS(accB, 46, { if constexpr (q < 2) G2_SEND(accA, 3, q * 2, q * 2 + 2) else if constexpr (q < 4) G2_OWN(accA + 32, 2, q * 2 - 4, q * 2 - 2) })
      G2_RLD(3, 0, 4)
      wg_wait<0>();
      PROF(10);
      G2_OWN(accB, 3, 0, 4)
    }
  }
}

typedef CUresult (*PFN_encodeTiled)(CUtensorMap*, CUtensorMapDataType, cuuint32_t, void*, const cuuint64_t*,
                                    const cuuint64_t*, const cuuint32_t*, const cuuint32_t*, CUtensorMapInterleave,
                                    CUtensorMapSwizzle, CUtensorMapL2promotion, CUtensorMapFloatOOBfill);

static void make_map(PFN_encodeTiled enc, CUtensorMap* m, const void* ptr, int rank, const cuuint64_t* dims,
                     const cuuint64_t* strides, const cuuint32_t* box) {
  cuuint32_t es[3] = {1, 1, 1};
  enc(m, CU_TENSOR_MAP_DATA_TYPE_BFLOAT16, rank, const_cast<void*>(ptr), dims, strides, box, es,
      CU_TENSOR_MAP_INTERLEAVE_NONE, CU_TENSOR_MAP_SWIZZLE_128B, CU_TENSOR_MAP_L2_PROMOTION_L2_128B,
      CU_TENSOR_MAP_FLOAT_OOB_FILL_NONE);
}

}

extern "C" void kernel_launch(void* const* d_in, const int* in_sizes, int n_in, void* d_out, int out_size) {
  using namespace fk;
  const __nv_bfloat16* x = (const __nv_bfloat16*)d_in[0];
  const __nv_bfloat16* wqkv = (const __nv_bfloat16*)d_in[1];
  const __nv_bfloat16* wo = (const __nv_bfloat16*)d_in[2];
  const __nv_bfloat16* wg = (const __nv_bfloat16*)d_in[4];
  const __nv_bfloat16* wu = (const __nv_bfloat16*)d_in[5];
  const __nv_bfloat16* wd = (const __nv_bfloat16*)d_in[6];
  __nv_bfloat16* out = (__nv_bfloat16*)d_out;

  static PFN_encodeTiled enc = nullptr;
  if (!enc) {
    void* fn = nullptr;
    cudaDriverEntryPointQueryResult qr;
    cudaGetDriverEntryPoint("cuTensorMapEncodeTiled", &fn, cudaEnableDefault, &qr);
    enc = (PFN_encodeTiled)fn;
    cudaFuncSetAttribute(fused_kernel, cudaFuncAttributeMaxDynamicSharedMemorySize, SMEM_BYTES);
  }
  Maps maps;
  {
    cuuint64_t d[2] = {D_, S_}, s[1] = {D_ * 2};
    cuuint32_t b[2] = {64, 128};
    make_map(enc, &maps.x, x, 2, d, s, b);
    make_map(enc, &maps.out, out, 2, d, s, b);
    cuuint32_t b64[2] = {64, 64};
    make_map(enc, &maps.out64, out, 2, d, s, b64);
  }
  {
    cuuint64_t d[3] = {D_, D_, 3}, s[2] = {3 * D_ * 2, D_ * 2};
    cuuint32_t b[3] = {64, 64, 3};
    make_map(enc, &maps.qkv, wqkv, 3, d, s, b);
    cuuint64_t d2[2] = {3 * D_, D_};
    make_map(enc, &maps.qkv2, wqkv, 2, d2, s, b);
  }
  {
    cuuint64_t d[2] = {DF_, D_}, s[1] = {DF_ * 2};
    cuuint32_t b[2] = {64, 64};
    make_map(enc, &maps.g, wg, 2, d, s, b);
    make_map(enc, &maps.u, wu, 2, d, s, b);
  }
  {
    cuuint64_t d[2] = {D_, D_}, s[1] = {D_ * 2};
    cuuint32_t b[2] = {64, 64};
    make_map(enc, &maps.wo, wo, 2, d, s, b);
    cuuint64_t d2[2] = {D_, DF_};
    make_map(enc, &maps.wd, wd, 2, d2, s, b);
  }
  fused_kernel<<<132, 384, SMEM_BYTES>>>(maps, wqkv, x, wo, wd, out);
}
```
